```python
import torch

def _softmax(x, axis=-1):
    return torch.softmax(x, dim=axis)
def _gelu(x):
    return torch.nn.functional.gelu(x, approximate="tanh")
def _silu(x):
    return torch.nn.functional.silu(x)
def _sigmoid(x):
    return torch.sigmoid(x)
def _layernorm(x, axis=-1, eps=1e-5):
    m = x.mean(dim=axis, keepdim=True)
    v = x.var(dim=axis, keepdim=True, unbiased=False)
    return (x - m) / torch.sqrt(v + eps)
def _scatter_add(tgt, idx, src, axis=0):
    return tgt.clone().index_add_(axis, idx, src)
def _segment_sum(src, seg, n):
    out = torch.zeros((n,) + src.shape[1:], dtype=src.dtype)
    return out.index_add_(0, seg, src)
def _pad(x, pw):
    flat = tuple(v for pair in reversed(pw) for v in pair)
    return torch.nn.functional.pad(x, flat)

kernel_name = 'recurrent_scan__ssm_conv_s5__glu_gated_bilinear__prompt'

def setup_inputs():

    _w = (lambda a: (lambda t: t.to(torch.bfloat16) if t.is_floating_point() else t)(torch.as_tensor(a)))
    def _A_setup():
        B, S, D = 1, 2048, 576
        P = D
        Lambda_re = -0.5 * (lambda _x: torch.exp(torch.as_tensor(_x)))((lambda *s: torch.randn(*s, dtype=torch.bfloat16) * 0.8)(P))
        Lambda_im = (lambda *s: torch.randn(*s, dtype=torch.bfloat16) * 0.8)(P) * 1.0
        B_re = (lambda *s: torch.randn(*s, dtype=torch.bfloat16) * 1.6)(P, D) * (D ** -0.5)
        B_im = (lambda *s: torch.randn(*s, dtype=torch.bfloat16) * 1.6)(P, D) * (D ** -0.5)
        C_re = (lambda *s: torch.randn(*s, dtype=torch.bfloat16) * 1.6)(D, P) * (P ** -0.5)
        C_im = (lambda *s: torch.randn(*s, dtype=torch.bfloat16) * 1.6)(D, P) * (P ** -0.5)
        log_dt = (lambda *s: torch.randn(*s, dtype=torch.bfloat16) * 0.8)(P) * 0.3 - 2.0
        Dskip = (lambda *s: torch.randn(*s, dtype=torch.bfloat16) * 0.8)(D)
        return {
            "x": _w((lambda *s: torch.randn(*s, dtype=torch.bfloat16) * 0.05)(B, S, D)),
            "Lambda_re": _w(Lambda_re),
            "Lambda_im": _w(Lambda_im),
            "B_re": _w(B_re),
            "B_im": _w(B_im),
            "C_re": _w(C_re),
            "C_im": _w(C_im),
            "log_dt": _w(log_dt),
            "Dskip": _w(Dskip),
        }
    _A_in = _A_setup()

    def _B_setup():
        B, S, D, F = 1, 2048, 576, 4608
        return {
            "x": _w((lambda *s: torch.randn(*s, dtype=torch.bfloat16) * 0.05)(B, S, D)),
            "w_gate": _w((lambda *s: torch.randn(*s, dtype=torch.bfloat16) * 0.2)(D, F) * (D ** -0.5)),
            "w_up": _w((lambda *s: torch.randn(*s, dtype=torch.bfloat16) * 0.2)(D, F) * (D ** -0.5)),
            "w_down": _w((lambda *s: torch.randn(*s, dtype=torch.bfloat16) * 0.2)(F, D) * (F ** -0.5)),
        }
    _B_in = _B_setup()

    return {
        "A_x": _A_in["x"],
        "A_Lambda_re": _A_in["Lambda_re"],
        "A_Lambda_im": _A_in["Lambda_im"],
        "A_B_re": _A_in["B_re"],
        "A_B_im": _A_in["B_im"],
        "A_C_re": _A_in["C_re"],
        "A_C_im": _A_in["C_im"],
        "A_log_dt": _A_in["log_dt"],
        "A_Dskip": _A_in["Dskip"],
        "B_x": _B_in["x"],
        "B_w_gate": _B_in["w_gate"],
        "B_w_up": _B_in["w_up"],
        "B_w_down": _B_in["w_down"],
    }

def reference(A_x, A_Lambda_re, A_Lambda_im, A_B_re, A_B_im, A_C_re, A_C_im, A_log_dt, A_Dskip, B_x, B_w_gate, B_w_up, B_w_down):
    def _A_ref(x, Lambda_re, Lambda_im, B_re, B_im, C_re, C_im, log_dt, Dskip):
        Bsz, L, H = x.shape
        Lam = Lambda_re + 1j * Lambda_im
        Bmat = B_re + 1j * B_im
        Cmat = C_re + 1j * C_im
        dt = torch.exp(log_dt)
        Lam_bar = torch.exp(dt * Lam)
        B_bar = ((Lam_bar - 1.0) / Lam)[:, None] * Bmat
        Bu = torch.einsum("bld,pd->blp", x + 0j, B_bar)
        h = torch.zeros_like(Bu[:, 0, :])
        hs = []
        for t in range(L):
            h = Lam_bar[None, :] * h + Bu[:, t, :]
            hs.append(h)
        hseq = torch.stack(hs, 1)
        y = 2.0 * torch.einsum("blp,dp->bld", hseq, Cmat).real + x * Dskip[None, None, :]
        return y

    def _B_ref(x, w_gate, w_up, w_down):
        g = torch.einsum("bsd,df->bsf", x, w_gate)
        u = torch.einsum("bsd,df->bsf", x, w_up)
        h = g * u
        return torch.einsum("bsf,fd->bsd", h, w_down)

    x = A_x
    xn = _layernorm(x, axis=-1)
    s = _A_ref(xn, A_Lambda_re, A_Lambda_im, A_B_re, A_B_im, A_C_re, A_C_im, A_log_dt, A_Dskip)
    g = _silu(_B_ref(xn, B_w_gate, B_w_up, B_w_down))
    return x + s * g
```

```cpp
#include <cuda_runtime.h>
#include <cuda.h>
#include <cuda_bf16.h>
#include <stdint.h>

namespace ssmffn {

constexpr int NCTA = 132, NREG = 128;
constexpr uint32_t OFF_RING = 147456, ST1 = 16384, NST1 = 5;
constexpr uint32_t ST2 = 34816, NST2 = 6;
constexpr uint32_t OFF_BAR = 229376;
constexpr uint32_t B_FULL1 = 0, B_EMPTY1 = 40, B_FULL2 = 80, B_EMPTY2 = 128, B_REL = 176  , B_PAR = 248,
                   B_E = 256  , B_CAR = 288  , B_XS = 320, W_TAG = 328;
constexpr uint32_t OFF_PAR = OFF_BAR + 336;
constexpr uint32_t OFF_CAR = OFF_PAR + 1024;
constexpr uint32_t OFF_STAT = OFF_CAR + 1024;
constexpr uint32_t SMEM_BYTES = OFF_STAT + 512;
constexpr uint32_t SPIN_LIMIT = 4000000;

__device__ __align__(1024) uint4 g_H[16 * 72 * 1024];
__device__ __align__(1024) uint4 g_HS[16 * 18 * 1024];
__device__ __align__(1024) uint4 g_WdT[4 * 72 * 1152];
__device__ __align__(1024) uint4 g_E[16 * 576];
__device__ __align__(1024) float4 g_XS[128 * 9 * 256];
__device__ __align__(1024) float4 g_XG[128 * 9 * 256];
__device__ __align__(1024) uint32_t g_flagH[128 * 8];
__device__ __align__(1024) uint32_t g_flagHS[16 * 9 * 8];
__device__ __align__(1024) uint32_t g_flagXS[128 * 8];
__device__ __align__(1024) uint32_t g_flagXG[128 * 8];
__device__ __align__(128) uint32_t g_cntW[32];
__device__ __align__(128) uint32_t g_done[32];
#define TR(id)
#define TRG(id)

struct Params {
  CUtensorMap WgA, WuA, WgB, WuB, Bre, Bim, Cre, Cim, X;
  const uint4* x;
  const __nv_bfloat16 *lre, *lim, *ldt;
  const uint32_t* dskip;
  const uint4* wd;
  float* out;
};

template<int TA, int TB> __device__ __forceinline__ void wgmma_n64(float (&d)[32], uint32_t alo, uint32_t blo, uint32_t hi, int sd, uint32_t hib = 0x40000040u) {
  asm volatile("{\n.reg .pred p;\n.reg .b64 da, db;\nsetp.ne.b32 p, %35, 0;\nmov.b64 da, {%32, %34};\nmov.b64 db, {%33, %38};\n"
    "wgmma.mma_async.sync.aligned.m64n64k16.f32.bf16.bf16 {%0, %1, %2, %3, %4, %5, %6, %7, %8, %9, %10, %11, %12, %13, %14, %15, %16, %17, %18, %19, %20, %21, %22, %23, %24, %25, %26, %27, %28, %29, %30, %31}, da, db, p, 1, 1, %36, %37;\n}\n"
    : "+f"(d[0]), "+f"(d[1]), "+f"(d[2]), "+f"(d[3]), "+f"(d[4]), "+f"(d[5]), "+f"(d[6]), "+f"(d[7]), "+f"(d[8]), "+f"(d[9]), "+f"(d[10]), "+f"(d[11]), "+f"(d[12]), "+f"(d[13]), "+f"(d[14]), "+f"(d[15]), "+f"(d[16]), "+f"(d[17]), "+f"(d[18]), "+f"(d[19]), "+f"(d[20]), "+f"(d[21]), "+f"(d[22]), "+f"(d[23]), "+f"(d[24]), "+f"(d[25]), "+f"(d[26]), "+f"(d[27]), "+f"(d[28]), "+f"(d[29]), "+f"(d[30]), "+f"(d[31])
    : "r"(alo), "r"(blo), "r"(hi), "r"(sd), "n"(TA), "n"(TB), "r"(hib));
}
template<int TA, int TB> __device__ __forceinline__ void wgmma_n128(float (&d)[64], uint32_t alo, uint32_t blo, uint32_t hi, int sd, uint32_t hib = 0x40000040u) {
  asm volatile("{\n.reg .pred p;\n.reg .b64 da, db;\nsetp.ne.b32 p, %67, 0;\nmov.b64 da, {%64, %66};\nmov.b64 db, {%65, %70};\n"
    "wgmma.mma_async.sync.aligned.m64n128k16.f32.bf16.bf16 {%0, %1, %2, %3, %4, %5, %6, %7, %8, %9, %10, %11, %12, %13, %14, %15, %16, %17, %18, %19, %20, %21, %22, %23, %24, %25, %26, %27, %28, %29, %30, %31, %32, %33, %34, %35, %36, %37, %38, %39, %40, %41, %42, %43, %44, %45, %46, %47, %48, %49, %50, %51, %52, %53, %54, %55, %56, %57, %58, %59, %60, %61, %62, %63}, da, db, p, 1, 1, %68, %69;\n}\n"
    : "+f"(d[0]), "+f"(d[1]), "+f"(d[2]), "+f"(d[3]), "+f"(d[4]), "+f"(d[5]), "+f"(d[6]), "+f"(d[7]), "+f"(d[8]), "+f"(d[9]), "+f"(d[10]), "+f"(d[11]), "+f"(d[12]), "+f"(d[13]), "+f"(d[14]), "+f"(d[15]), "+f"(d[16]), "+f"(d[17]), "+f"(d[18]), "+f"(d[19]), "+f"(d[20]), "+f"(d[21]), "+f"(d[22]), "+f"(d[23]), "+f"(d[24]), "+f"(d[25]), "+f"(d[26]), "+f"(d[27]), "+f"(d[28]), "+f"(d[29]), "+f"(d[30]), "+f"(d[31]), "+f"(d[32]), "+f"(d[33]), "+f"(d[34]), "+f"(d[35]), "+f"(d[36]), "+f"(d[37]), "+f"(d[38]), "+f"(d[39]), "+f"(d[40]), "+f"(d[41]), "+f"(d[42]), "+f"(d[43]), "+f"(d[44]), "+f"(d[45]), "+f"(d[46]), "+f"(d[47]), "+f"(d[48]), "+f"(d[49]), "+f"(d[50]), "+f"(d[51]), "+f"(d[52]), "+f"(d[53]), "+f"(d[54]), "+f"(d[55]), "+f"(d[56]), "+f"(d[57]), "+f"(d[58]), "+f"(d[59]), "+f"(d[60]), "+f"(d[61]), "+f"(d[62]), "+f"(d[63])
    : "r"(alo), "r"(blo), "r"(hi), "r"(sd), "n"(TA), "n"(TB), "r"(hib));
}
template<int TA, int TB> __device__ __forceinline__ void wgmma_n144(float (&d)[72], uint32_t alo, uint32_t blo, uint32_t hi, int sd, uint32_t hib = 0x40000040u) {
  asm volatile("{\n.reg .pred p;\n.reg .b64 da, db;\nsetp.ne.b32 p, %75, 0;\nmov.b64 da, {%72, %74};\nmov.b64 db, {%73, %78};\n"
    "wgmma.mma_async.sync.aligned.m64n144k16.f32.bf16.bf16 {%0, %1, %2, %3, %4, %5, %6, %7, %8, %9, %10, %11, %12, %13, %14, %15, %16, %17, %18, %19, %20, %21, %22, %23, %24, %25, %26, %27, %28, %29, %30, %31, %32, %33, %34, %35, %36, %37, %38, %39, %40, %41, %42, %43, %44, %45, %46, %47, %48, %49, %50, %51, %52, %53, %54, %55, %56, %57, %58, %59, %60, %61, %62, %63, %64, %65, %66, %67, %68, %69, %70, %71}, da, db, p, 1, 1, %76, %77;\n}\n"
    : "+f"(d[0]), "+f"(d[1]), "+f"(d[2]), "+f"(d[3]), "+f"(d[4]), "+f"(d[5]), "+f"(d[6]), "+f"(d[7]), "+f"(d[8]), "+f"(d[9]), "+f"(d[10]), "+f"(d[11]), "+f"(d[12]), "+f"(d[13]), "+f"(d[14]), "+f"(d[15]), "+f"(d[16]), "+f"(d[17]), "+f"(d[18]), "+f"(d[19]), "+f"(d[20]), "+f"(d[21]), "+f"(d[22]), "+f"(d[23]), "+f"(d[24]), "+f"(d[25]), "+f"(d[26]), "+f"(d[27]), "+f"(d[28]), "+f"(d[29]), "+f"(d[30]), "+f"(d[31]), "+f"(d[32]), "+f"(d[33]), "+f"(d[34]), "+f"(d[35]), "+f"(d[36]), "+f"(d[37]), "+f"(d[38]), "+f"(d[39]), "+f"(d[40]), "+f"(d[41]), "+f"(d[42]), "+f"(d[43]), "+f"(d[44]), "+f"(d[45]), "+f"(d[46]), "+f"(d[47]), "+f"(d[48]), "+f"(d[49]), "+f"(d[50]), "+f"(d[51]), "+f"(d[52]), "+f"(d[53]), "+f"(d[54]), "+f"(d[55]), "+f"(d[56]), "+f"(d[57]), "+f"(d[58]), "+f"(d[59]), "+f"(d[60]), "+f"(d[61]), "+f"(d[62]), "+f"(d[63]), "+f"(d[64]), "+f"(d[65]), "+f"(d[66]), "+f"(d[67]), "+f"(d[68]), "+f"(d[69]), "+f"(d[70]), "+f"(d[71])
    : "r"(alo), "r"(blo), "r"(hi), "r"(sd), "n"(TA), "n"(TB), "r"(hib));
}
template<int TA, int TB> __device__ __forceinline__ void wgmma_n256(float (&d)[128], uint32_t alo, uint32_t blo, uint32_t hi, int sd, uint32_t hib = 0x40000040u) {
  asm volatile("{\n.reg .pred p;\n.reg .b64 da, db;\nsetp.ne.b32 p, %131, 0;\nmov.b64 da, {%128, %130};\nmov.b64 db, {%129, %134};\n"
    "wgmma.mma_async.sync.aligned.m64n256k16.f32.bf16.bf16 {%0, %1, %2, %3, %4, %5, %6, %7, %8, %9, %10, %11, %12, %13, %14, %15, %16, %17, %18, %19, %20, %21, %22, %23, %24, %25, %26, %27, %28, %29, %30, %31, %32, %33, %34, %35, %36, %37, %38, %39, %40, %41, %42, %43, %44, %45, %46, %47, %48, %49, %50, %51, %52, %53, %54, %55, %56, %57, %58, %59, %60, %61, %62, %63, %64, %65, %66, %67, %68, %69, %70, %71, %72, %73, %74, %75, %76, %77, %78, %79, %80, %81, %82, %83, %84, %85, %86, %87, %88, %89, %90, %91, %92, %93, %94, %95, %96, %97, %98, %99, %100, %101, %102, %103, %104, %105, %106, %107, %108, %109, %110, %111, %112, %113, %114, %115, %116, %117, %118, %119, %120, %121, %122, %123, %124, %125, %126, %127}, da, db, p, 1, 1, %132, %133;\n}\n"
    : "+f"(d[0]), "+f"(d[1]), "+f"(d[2]), "+f"(d[3]), "+f"(d[4]), "+f"(d[5]), "+f"(d[6]), "+f"(d[7]), "+f"(d[8]), "+f"(d[9]), "+f"(d[10]), "+f"(d[11]), "+f"(d[12]), "+f"(d[13]), "+f"(d[14]), "+f"(d[15]), "+f"(d[16]), "+f"(d[17]), "+f"(d[18]), "+f"(d[19]), "+f"(d[20]), "+f"(d[21]), "+f"(d[22]), "+f"(d[23]), "+f"(d[24]), "+f"(d[25]), "+f"(d[26]), "+f"(d[27]), "+f"(d[28]), "+f"(d[29]), "+f"(d[30]), "+f"(d[31]), "+f"(d[32]), "+f"(d[33]), "+f"(d[34]), "+f"(d[35]), "+f"(d[36]), "+f"(d[37]), "+f"(d[38]), "+f"(d[39]), "+f"(d[40]), "+f"(d[41]), "+f"(d[42]), "+f"(d[43]), "+f"(d[44]), "+f"(d[45]), "+f"(d[46]), "+f"(d[47]), "+f"(d[48]), "+f"(d[49]), "+f"(d[50]), "+f"(d[51]), "+f"(d[52]), "+f"(d[53]), "+f"(d[54]), "+f"(d[55]), "+f"(d[56]), "+f"(d[57]), "+f"(d[58]), "+f"(d[59]), "+f"(d[60]), "+f"(d[61]), "+f"(d[62]), "+f"(d[63]), "+f"(d[64]), "+f"(d[65]), "+f"(d[66]), "+f"(d[67]), "+f"(d[68]), "+f"(d[69]), "+f"(d[70]), "+f"(d[71]), "+f"(d[72]), "+f"(d[73]), "+f"(d[74]), "+f"(d[75]), "+f"(d[76]), "+f"(d[77]), "+f"(d[78]), "+f"(d[79]), "+f"(d[80]), "+f"(d[81]), "+f"(d[82]), "+f"(d[83]), "+f"(d[84]), "+f"(d[85]), "+f"(d[86]), "+f"(d[87]), "+f"(d[88]), "+f"(d[89]), "+f"(d[90]), "+f"(d[91]), "+f"(d[92]), "+f"(d[93]), "+f"(d[94]), "+f"(d[95]), "+f"(d[96]), "+f"(d[97]), "+f"(d[98]), "+f"(d[99]), "+f"(d[100]), "+f"(d[101]), "+f"(d[102]), "+f"(d[103]), "+f"(d[104]), "+f"(d[105]), "+f"(d[106]), "+f"(d[107]), "+f"(d[108]), "+f"(d[109]), "+f"(d[110]), "+f"(d[111]), "+f"(d[112]), "+f"(d[113]), "+f"(d[114]), "+f"(d[115]), "+f"(d[116]), "+f"(d[117]), "+f"(d[118]), "+f"(d[119]), "+f"(d[120]), "+f"(d[121]), "+f"(d[122]), "+f"(d[123]), "+f"(d[124]), "+f"(d[125]), "+f"(d[126]), "+f"(d[127])
    : "r"(alo), "r"(blo), "r"(hi), "r"(sd), "n"(TA), "n"(TB), "r"(hib));
}

__device__ __forceinline__ uint32_t smem_u32(const void* p) { return (uint32_t)__cvta_generic_to_shared(p); }
__device__ __forceinline__ void mbar_init(uint32_t bar, uint32_t cnt) { asm volatile("mbarrier.init.shared::cta.b64 [%0], %1;" :: "r"(bar), "r"(cnt)); }
__device__ __forceinline__ void mbar_expect_tx(uint32_t bar, uint32_t bytes) { asm volatile("mbarrier.arrive.expect_tx.shared::cta.b64 _, [%0], %1;" :: "r"(bar), "r"(bytes) : "memory"); }
__device__ __forceinline__ void mbar_arrive(uint32_t bar) { asm volatile("mbarrier.arrive.shared::cta.b64 _, [%0];" :: "r"(bar) : "memory"); }
__device__ __forceinline__ void mbar_arrive_rem(uint32_t rbar) { asm volatile("mbarrier.arrive.shared::cluster.b64 _, [%0];" :: "r"(rbar) : "memory"); }
__device__ __forceinline__ void mbar_wait(uint32_t bar, uint32_t parity) {
  asm volatile("{\n.reg .pred p;\n.reg .u32 c;\n"
    "mbarrier.try_wait.parity.shared::cta.b64 p, [%0], %1;\n"
    "@p bra.uni DONE;\n"
    "mov.u32 c, 0;\n"
    "LOOP:\n"
    "mbarrier.try_wait.parity.shared::cta.b64 p, [%0], %1;\n"
    "@p bra.uni DONE;\n"
    "add.u32 c, c, 1;\n"
    "setp.lt.u32 p, c, %2;\n"
    "@p bra.uni LOOP;\n"
    "trap;\n"
    "DONE:\n}" :: "r"(bar), "r"(parity), "n"(SPIN_LIMIT) : "memory");
}
template<int SLEEP>
__device__ __forceinline__ uint32_t poll_ge(const uint32_t* p, uint32_t target) {
  uint32_t v;
  asm volatile("{\n.reg .pred p;\n.reg .u32 c;\n.reg .s32 d;\n"
    "mov.u32 c, 0;\n"
    "LOOP:\n"
    "ld.acquire.gpu.global.u32 %0, [%1];\n"
    "sub.s32 d, %0, %2;\n"
    "setp.ge.s32 p, d, 0;\n"
    "@p bra DONE;\n"
    "nanosleep.u32 %4;\n"
    "add.u32 c, c, 1;\n"
    "setp.lt.u32 p, c, %3;\n"
    "@p bra LOOP;\n"
    "trap;\n"
    "DONE:\n}" : "=&r"(v) : "l"(p), "r"(target), "n"(SPIN_LIMIT), "n"(SLEEP) : "memory");
  return v;
}
__device__ __forceinline__ void st_release(uint32_t* p, uint32_t v) { asm volatile("st.release.gpu.global.u32 [%0], %1;" :: "l"(p), "r"(v) : "memory"); }
__device__ __forceinline__ void red_release(uint32_t* p, uint32_t v) { asm volatile("red.release.gpu.global.add.u32 [%0], %1;" :: "l"(p), "r"(v) : "memory"); }
__device__ __forceinline__ uint32_t ld_relaxed(const uint32_t* p) { uint32_t v; asm volatile("ld.relaxed.gpu.global.u32 %0, [%1];" : "=r"(v) : "l"(p) : "memory"); return v; }
__device__ __forceinline__ void st_b128(uint4* p, uint32_t a, uint32_t b, uint32_t c, uint32_t d) {
  asm volatile("{\n.reg .b128 q;\n.reg .b64 l, h;\nmov.b64 l, {%1, %2};\nmov.b64 h, {%3, %4};\nmov.b128 q, {l, h};\nst.relaxed.gpu.global.b128 [%0], q;\n}"
    :: "l"(p), "r"(a), "r"(b), "r"(c), "r"(d) : "memory");
}
__device__ __forceinline__ uint4 ld_b128(const uint4* p) {
  uint4 v;
  asm volatile("{\n.reg .b128 q;\n.reg .b64 l, h;\nld.relaxed.gpu.global.b128 q, [%4];\nmov.b128 {l, h}, q;\nmov.b64 {%0, %1}, l;\nmov.b64 {%2, %3}, h;\n}"
    : "=r"(v.x), "=r"(v.y), "=r"(v.z), "=r"(v.w) : "l"(p) : "memory");
  return v;
}
__device__ __forceinline__ void fence_async_global() { asm volatile("fence.proxy.async.global;" ::: "memory"); }
__device__ __forceinline__ void fence_async_smem() { asm volatile("fence.proxy.async.shared::cta;" ::: "memory"); }
#define POLMASK 7
template<int ID> __device__ __forceinline__ uint64_t policy_stream() {
  uint64_t p;
  if ((POLMASK >> ID) & 1) asm volatile("createpolicy.fractional.L2::evict_first.b64 %0, 1.0;" : "=l"(p));
  else asm volatile("createpolicy.fractional.L2::evict_normal.b64 %0, 1.0;" : "=l"(p));
  return p;
}
__device__ __forceinline__ void tma2d(uint32_t dst, const CUtensorMap* m, int c0, int c1, uint32_t bar, uint64_t pol) {
  asm volatile("cp.async.bulk.tensor.2d.shared::cluster.global.mbarrier::complete_tx::bytes.L2::cache_hint [%0], [%1, {%3, %4}], [%2], %5;"
    :: "r"(dst), "l"(m), "r"(bar), "r"(c0), "r"(c1), "l"(pol) : "memory");
}
__device__ __forceinline__ void tma3d(uint32_t dst, const CUtensorMap* m, int c0, int c1, int c2, uint32_t bar, uint64_t pol) {
  asm volatile("cp.async.bulk.tensor.3d.shared::cluster.global.mbarrier::complete_tx::bytes.L2::cache_hint [%0], [%1, {%3, %4, %5}], [%2], %6;"
    :: "r"(dst), "l"(m), "r"(bar), "r"(c0), "r"(c1), "r"(c2), "l"(pol) : "memory");
}
__device__ __forceinline__ void tma_x(uint32_t dst, const CUtensorMap* m, int c0, int c4, uint32_t bar) {
  asm volatile("cp.async.bulk.tensor.5d.shared::cluster.global.mbarrier::complete_tx::bytes [%0], [%1, {%3, %5, %5, %5, %4}], [%2];"
    :: "r"(dst), "l"(m), "r"(bar), "r"(c0), "r"(c4), "r"(0) : "memory");
}
__device__ __forceinline__ void bulk_ld(uint32_t dst, const void* src, uint32_t bytes, uint32_t bar, uint64_t pol) {
  asm volatile("cp.async.bulk.shared::cluster.global.mbarrier::complete_tx::bytes.L2::cache_hint [%0], [%1], %2, [%3], %4;"
    :: "r"(dst), "l"(src), "r"(bytes), "r"(bar), "l"(pol) : "memory");
}
__device__ __forceinline__ void bulk_ld_mc(uint32_t dst, const void* src, uint32_t bytes, uint32_t bar, uint64_t pol) {
  asm volatile("cp.async.bulk.shared::cluster.global.mbarrier::complete_tx::bytes.multicast::cluster.L2::cache_hint [%0], [%1], %2, [%3], %4, %5;"
    :: "r"(dst), "l"(src), "r"(bytes), "r"(bar), "h"((uint16_t)3), "l"(pol) : "memory");
}
__device__ __forceinline__ void prefetch_map(const CUtensorMap* m) { asm volatile("prefetch.tensormap [%0];" :: "l"(m) : "memory"); }
__device__ __forceinline__ void wg_fence() { asm volatile("wgmma.fence.sync.aligned;" ::: "memory"); }
__device__ __forceinline__ void wg_commit() { asm volatile("wgmma.commit_group.sync.aligned;" ::: "memory"); }
template<int N> __device__ __forceinline__ void wg_wait() { asm volatile("wgmma.wait_group.sync.aligned %0;" :: "n"(N) : "memory"); }
template<int N> __device__ __forceinline__ void zero(float (&d)[N]) {
  #pragma unroll
  for (int i = 0; i < N; i++) d[i] = 0.f;
}
template<int N> __device__ __forceinline__ void pin(float (&d)[N]) {
  #pragma unroll
  for (int i = 0; i < N; i++) asm volatile("" : "+f"(d[i]) :: "memory");
}
__device__ __forceinline__ void cluster_arrive() { asm volatile("barrier.cluster.arrive.release.aligned;" ::: "memory"); }
__device__ __forceinline__ void cluster_wait() { asm volatile("barrier.cluster.wait.acquire.aligned;" ::: "memory"); }
__device__ __forceinline__ void bar_sync(int id, int n) { asm volatile("bar.sync %0, %1;" :: "r"(id), "r"(n) : "memory"); }
template<int R> __device__ __forceinline__ void reg_alloc() { asm volatile("setmaxnreg.inc.sync.aligned.u32 %0;" :: "n"(R)); }
template<int R> __device__ __forceinline__ void reg_dealloc() { asm volatile("setmaxnreg.dec.sync.aligned.u32 %0;" :: "n"(R)); }

__device__ __forceinline__ uint4 ldg_nc(const uint4* p, uint64_t pol) {
  uint4 v; asm volatile("ld.global.nc.L1::no_allocate.L2::cache_hint.v4.u32 {%0, %1, %2, %3}, [%4], %5;" : "=r"(v.x), "=r"(v.y), "=r"(v.z), "=r"(v.w) : "l"(p), "l"(pol)); return v;
}
__device__ __forceinline__ uint4 lds128(uint32_t a) {
  uint4 v; asm volatile("ld.shared.v4.u32 {%0, %1, %2, %3}, [%4];" : "=r"(v.x), "=r"(v.y), "=r"(v.z), "=r"(v.w) : "r"(a) : "memory"); return v;
}
__device__ __forceinline__ uint32_t ldg_nc32(const void* p) { uint32_t v; asm volatile("ld.global.nc.u32 %0, [%1];" : "=r"(v) : "l"(p)); return v; }
__device__ __forceinline__ float4 ldg_cg(const float4* p) {
  float4 v; asm volatile("ld.global.cg.v4.f32 {%0, %1, %2, %3}, [%4];" : "=f"(v.x), "=f"(v.y), "=f"(v.z), "=f"(v.w) : "l"(p) : "memory"); return v;
}
__device__ __forceinline__ void stg128(void* p, uint32_t a, uint32_t b, uint32_t c, uint32_t d) {
  asm volatile("st.global.v4.u32 [%0], {%1, %2, %3, %4};" :: "l"(p), "r"(a), "r"(b), "r"(c), "r"(d) : "memory");
}
__device__ __forceinline__ void stg128f(void* p, float a, float b, float c, float d) {
  asm volatile("st.global.v4.f32 [%0], {%1, %2, %3, %4};" :: "l"(p), "f"(a), "f"(b), "f"(c), "f"(d) : "memory");
}
__device__ __forceinline__ void sts128(uint32_t a, uint32_t x, uint32_t y, uint32_t z, uint32_t w) {
  asm volatile("st.shared.v4.u32 [%0], {%1, %2, %3, %4};" :: "r"(a), "r"(x), "r"(y), "r"(z), "r"(w) : "memory");
}
__device__ __forceinline__ void sts64f(uint32_t a, float x, float y) { asm volatile("st.shared.v2.f32 [%0], {%1, %2};" :: "r"(a), "f"(x), "f"(y) : "memory"); }
__device__ __forceinline__ float2 lds64f(uint32_t a) { float2 v; asm volatile("ld.shared.v2.f32 {%0, %1}, [%2];" : "=f"(v.x), "=f"(v.y) : "r"(a) : "memory"); return v; }
__device__ __forceinline__ uint32_t lds32(uint32_t a) { uint32_t v; asm volatile("ld.shared.u32 %0, [%1];" : "=r"(v) : "r"(a) : "memory"); return v; }
__device__ __forceinline__ uint32_t pack_bf16(float lo, float hi) { uint32_t r; asm("cvt.rn.bf16x2.f32 %0, %1, %2;" : "=r"(r) : "f"(hi), "f"(lo)); return r; }
__device__ __forceinline__ uint32_t bmul2(uint32_t a, uint32_t b) { uint32_t r; asm("mul.rn.bf16x2 %0, %1, %2;" : "=r"(r) : "r"(a), "r"(b)); return r; }
__device__ __forceinline__ uint32_t bsub2(uint32_t a, uint32_t b) { uint32_t r; asm("sub.rn.bf16x2 %0, %1, %2;" : "=r"(r) : "r"(a), "r"(b)); return r; }
__device__ __forceinline__ uint32_t bfma2(uint32_t a, uint32_t b, uint32_t c) { uint32_t r; asm("fma.rn.bf16x2 %0, %1, %2, %3;" : "=r"(r) : "r"(a), "r"(b), "r"(c)); return r; }
__device__ __forceinline__ float bf_lo(uint32_t v) { return __uint_as_float(v << 16); }
__device__ __forceinline__ float bf_hi(uint32_t v) { return __uint_as_float(v & 0xffff0000u); }
__device__ __forceinline__ float bf_round(float v) { return bf_lo(pack_bf16(v, 0.f)); }
__device__ __forceinline__ void mma_stat(float (&d)[4], uint32_t a, uint32_t b) {
  asm volatile("mma.sync.aligned.m16n8k16.row.col.f32.bf16.bf16.f32 {%0, %1, %2, %3}, {%4, %6, %5, %6}, {%4, %5}, {%0, %1, %2, %3};"
    : "+f"(d[0]), "+f"(d[1]), "+f"(d[2]), "+f"(d[3]) : "r"(a), "r"(b), "r"(0x3F803F80u));
}
__device__ __forceinline__ float2 cmul(float2 a, float2 b) { return make_float2(fmaf(a.x, b.x, -a.y * b.y), fmaf(a.x, b.y, a.y * b.x)); }
__device__ __forceinline__ float2 cfma(float2 a, float2 b, float2 c) { return make_float2(fmaf(a.x, b.x, fmaf(-a.y, b.y, c.x)), fmaf(a.x, b.y, fmaf(a.y, b.x, c.y))); }

__device__ __forceinline__ void ln_consts(uint32_t st, uint32_t& m2, uint32_t& rh2, uint32_t& rl2) {
  m2 = __byte_perm(st, st, 0x1010);
  float r; asm("rcp.approx.ftz.f32 %0, %1;" : "=f"(r) : "f"(bf_hi(st)));
  float rh = bf_round(r);
  rh2 = pack_bf16(rh, rh);
  rl2 = pack_bf16(r - rh, r - rh);
}
__device__ __forceinline__ uint32_t ln_apply(uint32_t x2, uint32_t m2, uint32_t rh2, uint32_t rl2) {
  uint32_t d = bsub2(x2, m2);
  return bfma2(d, rh2, bmul2(d, rl2));
}

struct LnC { uint32_t m2[2], rh2[2], rl2[2]; };
__device__ __forceinline__ void ln_stats(LnC& lc, uint32_t a0, uint32_t xbar, uint32_t par, uint32_t stat, int g, int c) {
  float d[2][2][4];
  #pragma unroll
  for (int i = 0; i < 16; i++) d[i >> 3][(i >> 2) & 1][i & 3] = 0.f;
  #pragma unroll 1
  for (int q = 0; q < 3; q++) {
    mbar_wait(xbar + 8 * q, par);
    #pragma unroll
    for (int kb = 0; kb < 3; kb++) {
      #pragma unroll
      for (int gi = 0; gi < 2; gi++) {
        const uint4 u = lds128(a0 + kb * 16384 + gi * 1024), v = lds128((a0 ^ 64) + kb * 16384 + gi * 1024);
        mma_stat(d[gi][0], u.x, u.y); mma_stat(d[gi][1], u.z, u.w);
        mma_stat(d[gi][0], v.x, v.y); mma_stat(d[gi][1], v.z, v.w);
      }
    }
    a0 += 3 * 16384;
  }
  const int o = g & 1, src = 4 * g + (g >> 1);
  #pragma unroll
  for (int gi = 0; gi < 2; gi++) {
    float sq = o ? (d[gi][0][1] + d[gi][1][1]) : (d[gi][0][0] + d[gi][1][0]);
    float sm = o ? (d[gi][0][3] + d[gi][1][3]) : (d[gi][0][2] + d[gi][1][2]);
    sq = __shfl_sync(0xffffffffu, sq, src);
    sm = __shfl_sync(0xffffffffu, sm, src);
    const float mean = sm * (1.0f / 576.0f);
    const float var = fmaxf(fmaf(-mean, mean, sq * (1.0f / 576.0f)), 0.f);
    float sd; asm("sqrt.approx.ftz.f32 %0, %1;" : "=f"(sd) : "f"(bf_round(bf_round(var) + 1e-5f)));
    const uint32_t st = pack_bf16(mean, sd);
    if (c == 0) asm volatile("st.shared.u32 [%0], %1;" :: "r"(stat + gi * 8), "r"(st) : "memory");
    ln_consts(st, lc.m2[gi], lc.rh2[gi], lc.rl2[gi]);
  }
}
__device__ __forceinline__ void ln_block(const LnC& lc, uint32_t a, int w) {
  uint4 v[4];
  #pragma unroll
  for (int i = 0; i < 4; i++) v[i] = lds128((a ^ ((i & 1) * 64)) + (i >> 1) * 1024);
  #pragma unroll
  for (int i = 0; i < 4; i++) {
    const uint32_t m2 = lc.m2[i >> 1], rh2 = lc.rh2[i >> 1], rl2 = lc.rl2[i >> 1];
    sts128((a ^ ((i & 1) * 64)) + (i >> 1) * 1024, ln_apply(v[i].x, m2, rh2, rl2), ln_apply(v[i].y, m2, rh2, rl2),
           ln_apply(v[i].z, m2, rh2, rl2), ln_apply(v[i].w, m2, rh2, rl2));
  }
  fence_async_smem();
  bar_sync(1 + w, 128);
}

struct Ring1 {
  uint32_t st, ph, full, soff, prev, base;
  __device__ __forceinline__ void init(uint32_t bars) { st = 0; ph = 0; full = bars + B_FULL1; base = full; soff = 0; prev = 0; }
  __device__ __forceinline__ void next() {
    prev = full + (B_EMPTY1 - B_FULL1);
    full += 8; soff += ST1 / 16;
    if (++st == NST1) { st = 0; ph ^= 1; full = base; soff = 0; }
  }
};
struct Ring2 {
  uint32_t st, ph, full, soff, prev, base;
  __device__ __forceinline__ void init(uint32_t bars) { st = 0; ph = 1; full = bars + B_FULL2; base = full; soff = 0; prev = 0; }
  __device__ __forceinline__ void next() {
    prev = full + (B_EMPTY2 - B_FULL2);
    full += 8; soff += ST2 / 16;
    if (++st == NST2) { st = 0; ph ^= 1; full = base; soff = 0; }
  }
};

constexpr uint32_t DHI = (1024 >> 4) | (1u << 30);

struct Scan {
  float2 lam[2], ex[2], pw[2];
};

template<int T0, int T1>
__device__ __forceinline__ void scan1(Scan& sc, const float (&XR)[32], const float (&XI)[32]) {
  #pragma unroll
  for (int t = T0; t < T1; t++)
    #pragma unroll
    for (int h = 0; h < 2; h++) {
      const int r = 4 * (t >> 1) + 2 * h + (t & 1);
      if (t == 0) sc.ex[h] = make_float2(XR[r], XI[r]);
      else sc.ex[h] = cfma(sc.lam[h], sc.ex[h], make_float2(XR[r], XI[r]));
    }
}
__device__ __forceinline__ void scan_combine(Scan& sc, uint32_t cara, int c) {
  #pragma unroll
  for (int h = 0; h < 2; h++) {
    float2 l16 = sc.lam[h];
    #pragma unroll
    for (int i = 0; i < 4; i++) l16 = cmul(l16, l16);
    const float2 l32 = cmul(l16, l16);
    float2 e = sc.ex[h], t;
    t.x = __shfl_up_sync(0xffffffffu, e.x, 1, 4); t.y = __shfl_up_sync(0xffffffffu, e.y, 1, 4);
    if (c >= 1) e = cfma(l16, t, e);
    t.x = __shfl_up_sync(0xffffffffu, e.x, 2, 4); t.y = __shfl_up_sync(0xffffffffu, e.y, 2, 4);
    if (c >= 2) e = cfma(l32, t, e);
    if (c == 3) sts64f(cara + h * 64, e.x, e.y);
    t.x = __shfl_up_sync(0xffffffffu, e.x, 1, 4); t.y = __shfl_up_sync(0xffffffffu, e.y, 1, 4);
    sc.ex[h] = c ? t : make_float2(0.f, 0.f);
    float2 pw = (c & 1) ? l16 : make_float2(1.f, 0.f);
    if (c & 2) pw = cmul(pw, l32);
    sc.pw[h] = pw;
  }
}
__device__ __forceinline__ void scan_carry(Scan& sc, uint32_t cara, uint32_t para) {
  #pragma unroll
  for (int h = 0; h < 2; h++) {
    sc.ex[h] = cfma(sc.pw[h], lds64f(cara + h * 64), sc.ex[h]);
    sc.pw[h] = lds64f(para + h * 128 + 8);
  }
}
template<int H8>
__device__ __forceinline__ void scan2(Scan& sc, const float (&XR)[32], const float (&XI)[32], uint8_t* hs) {
  uint32_t ore[2][4], oim[2][4];
  #pragma unroll
  for (int q = 0; q < 4; q++)
    #pragma unroll
    for (int h = 0; h < 2; h++) {
      const int r = 4 * (H8 * 4 + q) + 2 * h;
      const float2 a = cfma(sc.lam[h], sc.ex[h], make_float2(XR[r], XI[r]));
      const float2 b = cfma(sc.lam[h], a, make_float2(XR[r + 1], XI[r + 1]));
      sc.ex[h] = b;
      const float2 cf = sc.pw[h];
      ore[h][q] = pack_bf16(fmaf(cf.x, a.x, -cf.y * a.y), fmaf(cf.x, b.x, -cf.y * b.y));
      oim[h][q] = pack_bf16(fmaf(-cf.x, a.y, -cf.y * a.x), fmaf(-cf.x, b.y, -cf.y * b.x));
    }
  uint8_t* p = (uint8_t*)((uintptr_t)hs ^ (H8 << 4));
  #pragma unroll
  for (int h = 0; h < 2; h++) {
    stg128(p + h * 1024, ore[h][0], ore[h][1], ore[h][2], ore[h][3]);
    stg128(p + h * 1024 + 9 * 16384, oim[h][0], oim[h][1], oim[h][2], oim[h][3]);
  }
}

template<int N, int CH>
__device__ __forceinline__ void h_chunk(const float (&A)[N], uint8_t* p0, uint8_t* p1) {
  constexpr int h = CH & 1, a = (CH >> 1) & 1, kbl = CH >> 2;
  uint32_t o[4];
  #pragma unroll
  for (int jj = 0; jj < 4; jj++) {
    const int r = 4 * (8 * kbl + 4 * a + jj) + 2 * h;
    o[jj] = bmul2(pack_bf16(A[r], A[r + 1]), pack_bf16(A[N / 2 + r], A[N / 2 + r + 1]));
  }
  uint8_t* p = (uint8_t*)((uintptr_t)(h ? p1 : p0) ^ (a << 6)) + kbl * 16384;
  stg128(p, o[0], o[1], o[2], o[3]);
}

__device__ __forceinline__ void bu_stage(Ring1& rg, float (&XR)[32], float (&XI)[32], uint32_t lring, uint32_t lx, int sd) {
  mbar_wait(rg.full, rg.ph);
  wg_fence();
  #pragma unroll
  for (int k = 0; k < 4; k++) {
    wgmma_n64<0, 0>(XR, lring + rg.soff + k * 2, lx + k * 2, DHI, k ? 1 : sd);
    wgmma_n64<0, 0>(XI, lring + rg.soff + 512 + k * 2, lx + k * 2, DHI, k ? 1 : sd);
  }
  wg_commit();
}
__device__ __forceinline__ void ln_bu(Ring1& rg, float (&XR)[32], float (&XI)[32], uint32_t lring, uint32_t lxn, bool elected,
                                      uint32_t lna, uint32_t xbar, uint32_t par, uint32_t stat, int w, int g, int c) {
  LnC lc;
  ln_stats(lc, lna, xbar, par, stat, g, c);
  TR(1);
  ln_block(lc, lna, w);
  zero(XR); zero(XI);
  bu_stage(rg, XR, XI, lring, lxn, 0);
  rg.next();
  #pragma unroll 1
  for (uint32_t lx = lxn + 1024; lx != lxn + 9 * 1024; lx += 1024) {
    lna += 16384;
    ln_block(lc, lna, w);
    bu_stage(rg, XR, XI, lring, lx, 1);
    wg_wait<1>();
    if (elected) mbar_arrive(rg.prev);
    rg.next();
  }
}
__device__ __forceinline__ void a_stage(Ring1& rg, float (&Y)[128], uint32_t lx, uint32_t lringA, int sd, bool elected) {
  mbar_wait(rg.full, rg.ph);
  wg_fence();
  wgmma_n256<0, 1>(Y, lx, lringA + rg.soff, DHI, sd);
  wgmma_n256<0, 1>(Y, lx + 2, lringA + rg.soff + 128, DHI, 1);
  wg_commit();
  wg_wait<1>();
  if (elected) mbar_arrive(rg.prev);
  rg.next();
}
__device__ __forceinline__ void a_blocks(Ring1& rg, float (&Y)[128], uint32_t lxn, int kb0, int kb1, uint32_t lringA, bool elected) {
  #pragma unroll 1
  for (uint32_t lx = lxn + kb0 * 1024; lx != lxn + kb1 * 1024; lx += 1024) {
    a_stage(rg, Y, lx, lringA, 1, elected);
    a_stage(rg, Y, lx + 4, lringA, 1, elected);
  }
}
__device__ __forceinline__ void b_stage(Ring1& rg, float (&X)[64], uint32_t lx, uint32_t lringB, int sd, bool elected) {
  mbar_wait(rg.full, rg.ph);
  wg_fence();
  #pragma unroll
  for (int k = 0; k < 4; k++) wgmma_n128<0, 1>(X, lx + k * 2, lringB + rg.soff + k * 128, DHI, k ? 1 : sd);
  wg_commit();
  wg_wait<1>();
  if (elected) mbar_arrive(rg.prev);
  rg.next();
}

__global__ void __cluster_dims__(2, 1, 1) __launch_bounds__(384, 1) fused_kernel(const __grid_constant__ Params P) {
  extern __shared__ __align__(1024) uint8_t smem_raw[];
  const uint32_t sb = smem_u32(smem_raw);
  const uint32_t bars = sb + OFF_BAR;
  const int b = blockIdx.x;
  const int wid = __shfl_sync(0xffffffffu, threadIdx.x >> 5, 0);
  const int lane = threadIdx.x & 31;
  const bool regular = b < NREG;
  TR(0); TRG(30);
  if (threadIdx.x == 256) {
    if (sb & 1023) asm volatile("trap;");
    for (int i = 0; i < NST1; i++) { mbar_init(bars + B_FULL1 + 8 * i, 1); mbar_init(bars + B_EMPTY1 + 8 * i, 2); }
    for (int i = 0; i < NST2; i++) { mbar_init(bars + B_FULL2 + 8 * i, 1); mbar_init(bars + B_EMPTY2 + 8 * i, 4); }
    for (int i = 0; i < 9; i++) mbar_init(bars + B_REL + 8 * i, 8);
    mbar_init(bars + B_PAR, 2);
    mbar_init(bars + B_XS, 1);
    for (int i = 0; i < 4; i++) { mbar_init(bars + B_E + 8 * i, 8); mbar_init(bars + B_CAR + 8 * i, 2); }
    asm volatile("fence.mbarrier_init.release.cluster;" ::: "memory");
  }
  __syncthreads();
  cluster_arrive();

  if (wid >= 8) {
    reg_dealloc<40>();
    const int blk = regular ? (b & 7) : 8;
    if (wid == 8) {
      if (lane == 0) {
        uint32_t st = 0, ph = 1;
        const uint64_t pol = policy_stream<0>();
        const int nbu = regular ? 1 : 4;
#pragma unroll 1
        for (int r = 0; r < nbu; r++) {
          const int m2 = regular ? (b >> 3) * 2 : (4 * r + b - NREG) * 2;
          if (r > 0) mbar_wait(bars + B_E + 8 * (r - 1), 0);
#pragma unroll 1
          for (int s = 0; s < 9; s++) {
            if (s < 2) {
#pragma unroll 1
              for (int kb = 0; kb < 9; kb++) {
                const uint32_t xb = bars + B_FULL2 + s * 24 + (kb / 3) * 8;
                if (kb % 3 == 0) mbar_expect_tx(xb, 3 * 8192);
                tma_x(sb + kb * 16384 + s * 8192, &P.X, kb * 64, m2 + s, xb);
              }
            }
            const uint32_t fb = bars + B_FULL1 + 8 * st, dst = sb + OFF_RING + st * ST1;
            mbar_wait(bars + B_EMPTY1 + 8 * st, ph);
            mbar_expect_tx(fb, ST1);
            tma2d(dst, &P.Bre, s * 64, blk * 64, fb, pol);
            tma2d(dst + 8192, &P.Bim, s * 64, blk * 64, fb, pol);
            if (++st == NST1) { st = 0; ph ^= 1; }
          }
        }
        if (regular) {
#pragma unroll 1
          for (int it = 0; it < 3; it++) {
            const int cb = blk * 9 + it * 3;
#pragma unroll 1
            for (int s = 0; s < 27; s++) {
              const uint32_t fb = bars + B_FULL1 + 8 * st, dst = sb + OFF_RING + st * ST1;
              mbar_wait(bars + B_EMPTY1 + 8 * st, ph);
              mbar_expect_tx(fb, ST1);
              if (s < 18) {
                tma3d(dst, &P.WgA, 0, s * 32, cb, fb, pol);
                tma3d(dst + 8192, &P.WuA, 0, s * 32, cb, fb, pol);
              } else {
                tma2d(dst, &P.WgB, (cb + 2) * 64, (s - 18) * 64, fb, pol);
                tma2d(dst + 8192, &P.WuB, (cb + 2) * 64, (s - 18) * 64, fb, pol);
              }
              if (++st == NST1) { st = 0; ph ^= 1; }
            }
          }
        }
      }
      __syncwarp();
      cluster_wait();
    } else {
      const uint32_t tag = ld_relaxed(g_done) / NCTA + 1;
      if (wid == 9) {
        if (lane < 9) prefetch_map(&P.WgA + lane);
        if (regular) mbar_wait(bars + B_E, 0);
      } else {
        const int pl = (wid - 10) * 32 + lane, p = blk * 64 + pl;
        const float lre = __bfloat162float(P.lre[p]), lim = __bfloat162float(P.lim[p]);
        const float dt = bf_round(expf(__bfloat162float(P.ldt[p])));
        const float er = expf(dt * lre);
        float sn, cs;
        sincosf(dt * lim, &sn, &cs);
        const float2 lam = make_float2(er * cs, er * sn);
        const float nr = lam.x - 1.0f, ni = lam.y, den = 2.0f / (lre * lre + lim * lim);
        sts64f(sb + OFF_PAR + pl * 16, lam.x, lam.y);
        sts64f(sb + OFF_PAR + pl * 16 + 8, (nr * lre + ni * lim) * den, (ni * lre - nr * lim) * den);
        if (lane == 0) asm volatile("st.shared.u32 [%0], %1;" :: "r"(bars + W_TAG), "r"(tag) : "memory");
        __syncwarp();
        if (lane == 0) mbar_arrive(bars + B_PAR);
        float2 l64 = lam;
        #pragma unroll
        for (int i = 0; i < 6; i++) l64 = cmul(l64, l64);
        const float2 l128 = cmul(l64, l64);
        const int nr_ = regular ? 1 : 4;
#pragma unroll 1
        for (int r = 0; r < nr_; r++) {
          const int m = regular ? (b >> 3) : (4 * r + b - NREG);
          mbar_wait(bars + B_E + 8 * r, 0);
          TR(3);
          const float2 e0 = lds64f(sb + OFF_CAR + pl * 8), e1 = lds64f(sb + OFF_CAR + 512 + pl * 8);
          const float2 e = cfma(l64, e0, e1);
          st_b128(g_E + m * 576 + p, __float_as_uint(e.x), __float_as_uint(e.y), tag, tag);
          float2 cy = make_float2(0.f, 0.f);
#pragma unroll 1
          for (int i0 = 0; i0 < m; i0 += 5) {
            uint4 q[5];
            for (uint32_t spin = 0;; spin++) {
              #pragma unroll
              for (int i = 0; i < 5; i++) q[i] = ld_b128(g_E + min(i0 + i, m - 1) * 576 + p);
              bool ok = true;
              #pragma unroll
              for (int i = 0; i < 5; i++) ok = ok && (q[i].z == tag);
              if (ok) break;
              if (spin > SPIN_LIMIT) asm volatile("trap;");
            }
            #pragma unroll
            for (int i = 0; i < 5; i++)
              if (i0 + i < m) cy = cfma(l128, cy, make_float2(__uint_as_float(q[i].x), __uint_as_float(q[i].y)));
            TR(4 + i0 / 5);
          }
          const float2 c1 = cfma(l64, cy, e0);
          sts64f(sb + OFF_CAR + pl * 8, cy.x, cy.y);
          sts64f(sb + OFF_CAR + 512 + pl * 8, c1.x, c1.y);
          __syncwarp();
          if (lane == 0) mbar_arrive(bars + B_CAR + 8 * r);
          TR(1);
          if (!regular) {
            mbar_wait(bars + B_REL + 8 * r, 0);
            if (wid == 10 && lane == 0) { __threadfence(); st_release(g_flagHS + (m * 9 + 8) * 8, tag); }
          }
        }
      }
      if (regular) {
        const uint64_t pol = policy_stream<1>();
#pragma unroll 1
        for (int u = b * 3 + (wid - 9); u < 1152; u += NREG * 3) {
          const int kb = u >> 4, kg = (u >> 1) & 7, r = (u & 1) * 4 + (lane >> 3);
          const int f = kb * 64 + 32 * (kg >> 2) + 8 * (r >> 1) + 2 * (kg & 3) + (r & 1);
          const uint4* src = P.wd + (size_t)f * 72 + (lane & 7);
          uint4* dst = g_WdT + kb * 1152 + kg * 144 + r;
#pragma unroll 1
          for (int i0 = 0; i0 < 9; i0 += 3) {
            uint4 v[3];
            #pragma unroll
            for (int i = 0; i < 3; i++) v[i] = ldg_nc(src + (i0 + i) * 8, pol);
            TR(10 + (u / 384) * 6 + (i0 / 3) * 2);
            #pragma unroll
            for (int i = 0; i < 3; i++) {
              const int nb = (i0 + i) * 8 + (lane & 7), nt = nb / 18;
              stg128(dst + nt * (72 * 1152) + (nb - nt * 18) * 8, v[i].x, v[i].y, v[i].z, v[i].w);
            }
            TR(11 + (u / 384) * 6 + (i0 / 3) * 2);
          }
        }
        __syncwarp();
        if (lane == 0) { __threadfence(); red_release(g_cntW, 1); }
        TR(2);
      }
      cluster_wait();
      if (regular) {
        const int m = b >> 3;
        if (wid == 10) {
          if (lane == 0) {
            mbar_wait(bars + B_REL, 0);
            __threadfence(); st_release(g_flagHS + (m * 9 + blk) * 8, tag);
#pragma unroll 1
            for (int i = 1; i < 7; i++) {
              mbar_wait(bars + B_REL + 8 * i, 0);
              __threadfence(); st_release(g_flagH + b * 8, tag * 16 + (3 * i + 1) / 2);
            }
            mbar_wait(bars + B_REL + 56, 0);
            __threadfence(); st_release(g_flagXS + b * 8, tag);
            mbar_wait(bars + B_REL + 64, 0);
            __threadfence(); st_release(g_flagXG + b * 8, tag);
          }
        } else if (wid == 11) {
          if (lane == 0) { poll_ge<200>(g_flagXS + (b ^ 4) * 8, tag); mbar_arrive(bars + B_XS); }
        } else {
          const int rank = b & 1, n = b & 3, kh = (b >> 2) & 1;
          if (lane == 0) poll_ge<200>(g_cntW, tag * (NREG * 3));
          uint32_t lvl = 0, st = 0, ph = 0;
          const uint64_t pol = policy_stream<2>();
#pragma unroll 1
          for (int i = 0; i < 45; i++) {
            const bool isg = i < 16 || i >= 25;
            const int gi = i < 16 ? i : i - 9;
            const int kb = gi >> 2;
            if (isg) {
              if (lvl <= (uint32_t)kb) {
                uint32_t v = 15;
                if (lane < 4) v = poll_ge<100>(g_flagH + (m * 8 + kh * 4 + lane) * 8, tag * 16 + kb + 1) - tag * 16;
                lvl = __reduce_min_sync(0xffffffffu, v);
                fence_async_global();
              }
            } else if (i == 16) {
              if (lane < 9) poll_ge<100>(g_flagHS + (m * 9 + lane) * 8, tag);
              __syncwarp();
              fence_async_global();
            }
            if (lane == 0) {
              const uint32_t fb = bars + B_FULL2 + 8 * st, dst = sb + st * ST2;
              mbar_wait(bars + B_EMPTY2 + 8 * st, ph);
              mbar_expect_tx(fb, ST2);
              if (isg) {
                const int kk = (kh * 4 + (gi & 3)) * 9 + kb;
                bulk_ld_mc(dst + rank * 8192, (const uint8_t*)g_H + (size_t)(m * 72 + kk) * 16384 + rank * 8192, 8192, fb, pol);
                bulk_ld(dst + 16384, (const uint8_t*)g_WdT + (size_t)(n * 72 + kk) * 18432, 18432, fb, pol);
              } else {
                bulk_ld_mc(dst + rank * 8192, (const uint8_t*)g_HS + (size_t)(m * 18 + kh * 9 + i - 16) * 16384 + rank * 8192, 8192, fb, pol);
                tma2d(dst + 16384, kh ? &P.Cim : &P.Cre, (i - 16) * 64, n * 144, fb, pol);
              }
            }
            __syncwarp();
            if (++st == NST2) { st = 0; ph ^= 1; }
          }
        }
      }
    }
  } else {
    reg_alloc<232>();
    const int w = wid >> 2, warp = wid & 3, g = lane >> 2, c = lane & 3;
    const bool elected = (threadIdx.x & 127) == 0;
    const uint32_t sd16 = (sb & 0x3FFFF) >> 4;
    const uint32_t lring = (sd16 + (OFF_RING >> 4)) | (1u << 16);
    const uint32_t lxn = (sd16 + w * 512) | (1u << 16);
    const uint32_t para = sb + OFF_PAR + (warp * 16 + g) * 16;
    const uint32_t cara = sb + OFF_CAR + w * 512 + (warp * 16 + g) * 8;
    const uint32_t hs_off = w * 8192 + (warp * 16 + g) * 128 + (((2 * c) ^ g) << 4);
    const uint32_t lna = sb + w * 8192 + (warp * 16 + g) * 128 + (c + 4 * (g & 1)) * 16;
    const uint32_t xbar = bars + B_FULL2 + w * 24;
    const uint32_t stata = sb + OFF_STAT + (w * 64 + 16 * (g >> 1) + 4 * warp + (g & 1)) * 4;
    Ring1 rg; rg.init(bars);
    if (!regular) {
      #pragma unroll 1
      for (int r = 0; r < 4; r++) {
        const int m = 4 * r + b - NREG;
        float XR[32], XI[32];
        ln_bu(rg, XR, XI, lring, lxn, elected, lna, xbar, r & 1, stata, w, g, c);
        wg_wait<0>();
        if (elected) mbar_arrive(rg.prev);
        pin(XR); pin(XI);
        Scan sc;
        mbar_wait(bars + B_PAR, 0);
        sc.lam[0] = lds64f(para); sc.lam[1] = lds64f(para + 128);
        scan1<0, 16>(sc, XR, XI);
        scan_combine(sc, cara, c);
        __syncwarp();
        if (lane == 0) mbar_arrive(bars + B_E + 8 * r);
        mbar_wait(bars + B_CAR + 8 * r, 0);
        scan_carry(sc, cara, para);
        uint8_t* hs = (uint8_t*)g_HS + (size_t)(m * 18 + 8) * 16384 + hs_off;
        scan2<0>(sc, XR, XI, hs);
        scan2<1>(sc, XR, XI, hs);
        __syncwarp();
        if (lane == 0) mbar_arrive(bars + B_REL + 8 * r);
        TR(2 + r);
      }
      cluster_wait();
    } else {
      const int m = b >> 3, j = b & 7;
      float Y[128];
      const uint32_t lringA = (sd16 + (OFF_RING >> 4)) | ((4096u >> 4) << 16);
      const uint32_t lringB = (sd16 + (OFF_RING >> 4)) | ((8192u >> 4) << 16);
      {
        float XR[32], XI[32];
        ln_bu(rg, XR, XI, lring, lxn, elected, lna, xbar, 0, stata, w, g, c);
        TR(2);
        Scan sc;
        uint8_t* hs = (uint8_t*)g_HS + (size_t)(m * 18 + j) * 16384 + hs_off;
        zero(Y);
        a_stage(rg, Y, lxn, lringA, 0, elected);
        pin(XR); pin(XI);
        mbar_wait(bars + B_PAR, 0);
        sc.lam[0] = lds64f(para); sc.lam[1] = lds64f(para + 128);
        scan1<0, 16>(sc, XR, XI);
        a_stage(rg, Y, lxn + 4, lringA, 1, elected);
        scan_combine(sc, cara, c);
        __syncwarp();
        if (lane == 0) mbar_arrive(bars + B_E);
        a_blocks(rg, Y, lxn, 1, 7, lringA, elected);
        TR(3); mbar_wait(bars + B_CAR, 0); TR(4);
        scan_carry(sc, cara, para);
        a_stage(rg, Y, lxn + 7 * 1024, lringA, 1, elected);
        pin(XR); pin(XI); scan2<0>(sc, XR, XI, hs);
        a_stage(rg, Y, lxn + 7 * 1024 + 4, lringA, 1, elected);
        pin(XR); pin(XI); scan2<1>(sc, XR, XI, hs);
        __syncwarp();
        if (lane == 0) mbar_arrive(bars + B_REL);
        a_stage(rg, Y, lxn + 8 * 1024, lringA, 1, elected);
        a_stage(rg, Y, lxn + 8 * 1024 + 4, lringA, 1, elected);
      }
      TR(5);
      cluster_wait();
      uint32_t rdelta;
      { uint32_t ra; asm("mapa.shared::cluster.u32 %0, %1, %2;" : "=r"(ra) : "r"(bars), "r"((b & 1) ^ 1)); rdelta = ra - bars; }
      const int tl0 = 16 * (g >> 1) + 4 * warp + (g & 1);
      uint8_t* hp0 = (uint8_t*)g_H + (size_t)(m * 72 + j * 9) * 16384 + (w * 64 + tl0) * 128 + ((c ^ (tl0 & 7)) << 4);
      uint8_t* hp1 = (uint8_t*)g_H + (size_t)(m * 72 + j * 9) * 16384 + (w * 64 + tl0 + 2) * 128 + ((c ^ ((tl0 + 2) & 7)) << 4);
      float X[64];
      uint32_t relb = bars + B_REL + 8;
      #pragma unroll 1
      for (int it = 0;; it++) {
        zero(X);
        b_stage(rg, X, lxn, lringB, 0, elected);
        pin(Y); h_chunk<128, 0>(Y, hp0, hp1); h_chunk<128, 2>(Y, hp0, hp1); h_chunk<128, 1>(Y, hp0, hp1);
        b_stage(rg, X, lxn + 1024, lringB, 1, elected);
        pin(Y); h_chunk<128, 3>(Y, hp0, hp1); h_chunk<128, 4>(Y, hp0, hp1); h_chunk<128, 6>(Y, hp0, hp1);
        b_stage(rg, X, lxn + 2048, lringB, 1, elected);
        pin(Y); h_chunk<128, 5>(Y, hp0, hp1); h_chunk<128, 7>(Y, hp0, hp1);
        __syncwarp();
        if (lane == 0) mbar_arrive(relb);
        relb += 8; hp0 += 32768; hp1 += 32768;
        uint32_t eb = bars + B_EMPTY2;
        #pragma unroll 1
        for (uint32_t lx = lxn + 3 * 1024; lx != lxn + 9 * 1024; lx += 2048) {
          b_stage(rg, X, lx, lringB, 1, elected);
          if (it == 2 && elected) { mbar_arrive(eb); mbar_arrive_rem(eb + rdelta); }
          eb += 8;
          b_stage(rg, X, lx + 1024, lringB, 1, elected);
        }
        TR(6 + 2 * it);
        if (it == 2) break;
        zero(Y);
        a_stage(rg, Y, lxn, lringA, 0, elected);
        pin(X); h_chunk<64, 0>(X, hp0, hp1); h_chunk<64, 2>(X, hp0, hp1);
        a_stage(rg, Y, lxn + 4, lringA, 1, elected);
        pin(X); h_chunk<64, 1>(X, hp0, hp1); h_chunk<64, 3>(X, hp0, hp1);
        __syncwarp();
        if (lane == 0) mbar_arrive(relb);
        relb += 8; hp0 += 16384; hp1 += 16384;
        a_blocks(rg, Y, lxn, 1, 9, lringA, elected);
        TR(7 + 2 * it);
      }
      const int n = b & 3, kh = (b >> 2) & 1;
      float G[72], S[72];
      Ring2 r2; r2.init(bars);
      #pragma unroll
      for (int i = 0; i < 72; i++) G[i] = Y[i];
      int sd0; asm volatile("mov.u32 %0, 0;" : "=r"(sd0));
      const uint32_t la2 = lxn;
      const uint32_t lb2 = (sd16 + 1024) | (1u << 16);
      const uint32_t lbw = (sd16 + 1024) | ((2304u >> 4) << 16);
      auto g_stage = [&](int first) {
        mbar_wait(r2.full, r2.ph);
        wg_fence();
        #pragma unroll
        for (int k = 0; k < 4; k++) wgmma_n144<0, 1>(G, la2 + r2.soff + k * 2, lbw + r2.soff + k * 288, DHI, (first && k == 0) ? sd0 : 1, 8u);
        wg_commit();
        wg_wait<1>();
      };
      auto rel2 = [&]() { if (elected) { mbar_arrive(r2.prev); mbar_arrive_rem(r2.prev + rdelta); } };
      g_stage(1);
      if (elected) {
        #pragma unroll
        for (int q = 3; q < 6; q++) { mbar_arrive(bars + B_EMPTY2 + 8 * q); mbar_arrive_rem(bars + B_EMPTY2 + 8 * q + rdelta); }
      }
      r2.next();
      pin(X); h_chunk<64, 0>(X, hp0, hp1); h_chunk<64, 2>(X, hp0, hp1); h_chunk<64, 1>(X, hp0, hp1); h_chunk<64, 3>(X, hp0, hp1);
      __syncwarp();
      if (lane == 0) mbar_arrive(bars + B_REL + 48);
      TR(12);
      #pragma unroll 1
      for (int i = 1; i < 16; i++) { g_stage(0); rel2(); r2.next(); }
      TR(13);
      zero(S);
      #pragma unroll 1
      for (int i = 0; i < 9; i++) {
        mbar_wait(r2.full, r2.ph);
        wg_fence();
        #pragma unroll
        for (int k = 0; k < 4; k++) wgmma_n144<1, 0>(S, la2 + r2.soff + k * 128, lb2 + r2.soff + k * 2, DHI, 1);
        wg_commit();
        wg_wait<1>();
        rel2(); r2.next();
      }
      TR(14);
      g_stage(0); rel2(); r2.next();
      pin(S);
      float K[36];
      {
        float4* xs = g_XS + (size_t)b * 2304 + threadIdx.x;
        if (kh) {
          #pragma unroll
          for (int q = 0; q < 9; q++) stg128f(xs + q * 256, S[4 * q], S[4 * q + 1], S[4 * q + 2], S[4 * q + 3]);
          #pragma unroll
          for (int q = 0; q < 36; q++) K[q] = S[36 + q];
        } else {
          #pragma unroll
          for (int q = 0; q < 9; q++) stg128f(xs + q * 256, S[36 + 4 * q], S[37 + 4 * q], S[38 + 4 * q], S[39 + 4 * q]);
          #pragma unroll
          for (int q = 0; q < 36; q++) K[q] = S[q];
        }
        __syncwarp();
        if (lane == 0) mbar_arrive(bars + B_REL + 56);
      }
      const int row0 = w * 64 + warp * 16 + g;
      const int col0 = n * 144 + kh * 72 + 2 * c;
      uint32_t xv[18];
      g_stage(0); rel2(); r2.next();
      {
        uint32_t dv[9];
        const uint8_t* xp = (const uint8_t*)P.x + ((size_t)(m * 128 + row0) * 576 + col0) * 2;
        #pragma unroll
        for (int q = 0; q < 9; q++) {
          xv[2 * q] = ldg_nc32(xp + q * 16);
          xv[2 * q + 1] = ldg_nc32(xp + q * 16 + 8 * 1152);
          dv[q] = ldg_nc32((const uint8_t*)P.dskip + col0 * 2 + q * 16);
        }
        g_stage(0); rel2(); r2.next();
        g_stage(0); rel2(); r2.next();
        #pragma unroll
        for (int h = 0; h < 2; h++) {
          uint32_t m2, rh2, rl2;
          ln_consts(lds32(sb + OFF_STAT + (row0 + 8 * h) * 4), m2, rh2, rl2);
          #pragma unroll
          for (int q = 0; q < 9; q++) {
            const uint32_t t = bmul2(ln_apply(xv[2 * q + h], m2, rh2, rl2), dv[q]);
            K[4 * q + 2 * h] += bf_lo(t);
            K[4 * q + 2 * h + 1] += bf_hi(t);
          }
        }
      }
      #pragma unroll 1
      for (int i = 29; i < 34; i++) { g_stage(0); rel2(); r2.next(); }
      {
        TR(15);
        mbar_wait(bars + B_XS, 0);
        TR(16);
        float4 t[9];
        const float4* xs = g_XS + (size_t)(b ^ 4) * 2304 + threadIdx.x;
        #pragma unroll
        for (int q = 0; q < 9; q++) t[q] = ldg_cg(xs + q * 256);
        g_stage(0); rel2(); r2.next();
        g_stage(0); rel2(); r2.next();
        #pragma unroll
        for (int q = 0; q < 9; q++) { K[4 * q] += t[q].x; K[4 * q + 1] += t[q].y; K[4 * q + 2] += t[q].z; K[4 * q + 3] += t[q].w; }
      }
      #pragma unroll 1
      for (int i = 36; i < 45; i++) { g_stage(0); if (i < 40) rel2(); r2.next(); }
      wg_wait<0>();
      pin(G);
      TR(17);
      float GK[36];
      {
        float4* xg = g_XG + (size_t)b * 2304 + threadIdx.x;
        if (kh) {
          #pragma unroll
          for (int q = 0; q < 9; q++) stg128f(xg + q * 256, G[4 * q], G[4 * q + 1], G[4 * q + 2], G[4 * q + 3]);
          #pragma unroll
          for (int q = 0; q < 36; q++) GK[q] = G[36 + q];
        } else {
          #pragma unroll
          for (int q = 0; q < 9; q++) stg128f(xg + q * 256, G[36 + 4 * q], G[37 + 4 * q], G[38 + 4 * q], G[39 + 4 * q]);
          #pragma unroll
          for (int q = 0; q < 36; q++) GK[q] = G[q];
        }
        __syncwarp();
        if (lane == 0) { mbar_arrive(bars + B_REL + 64); poll_ge<0>(g_flagXG + (b ^ 4) * 8, lds32(bars + W_TAG)); }
        __syncwarp();
        TR(18);
        const float4* xr = g_XG + (size_t)(b ^ 4) * 2304 + threadIdx.x;
        float4 t[9];
        #pragma unroll
        for (int q = 0; q < 9; q++) t[q] = ldg_cg(xr + q * 256);
        float* op = P.out + (size_t)(m * 128 + row0) * 576 + col0;
        #pragma unroll
        for (int q = 0; q < 9; q++) {
          const float gs[4] = {GK[4 * q] + t[q].x, GK[4 * q + 1] + t[q].y, GK[4 * q + 2] + t[q].z, GK[4 * q + 3] + t[q].w};
          #pragma unroll
          for (int h = 0; h < 2; h++) {
            const uint32_t gb = pack_bf16(gs[2 * h], gs[2 * h + 1]);
            const float g0 = bf_lo(gb), g1 = bf_hi(gb);
            const uint32_t sg = pack_bf16(__fdividef(g0, 1.0f + __expf(-g0)), __fdividef(g1, 1.0f + __expf(-g1)));
            const float o0 = fmaf(K[4 * q + 2 * h], bf_lo(sg), bf_lo(xv[2 * q + h]));
            const float o1 = fmaf(K[4 * q + 2 * h + 1], bf_hi(sg), bf_hi(xv[2 * q + h]));
            *(float2*)(op + q * 8 + h * 8 * 576) = make_float2(o0, o1);
          }
        }
      }
      TR(19); TRG(31);
    }
    bar_sync(3, 256);
    if (threadIdx.x == 0) atomicAdd(g_done, 1);
  }
}

typedef CUresult (*EncodeFn)(CUtensorMap*, CUtensorMapDataType, cuuint32_t, void*, const cuuint64_t*, const cuuint64_t*,
                             const cuuint32_t*, const cuuint32_t*, CUtensorMapInterleave, CUtensorMapSwizzle,
                             CUtensorMapL2promotion, CUtensorMapFloatOOBfill);

static void make_map(EncodeFn enc, CUtensorMap* m, const void* base, int rank, const cuuint64_t* dims, const cuuint64_t* strides, const cuuint32_t* box) {
  cuuint32_t es[5] = {1, 1, 1, 1, 1};
  enc(m, CU_TENSOR_MAP_DATA_TYPE_BFLOAT16, rank, (void*)base, dims, strides, box, es, CU_TENSOR_MAP_INTERLEAVE_NONE,
      CU_TENSOR_MAP_SWIZZLE_128B, CU_TENSOR_MAP_L2_PROMOTION_L2_256B, CU_TENSOR_MAP_FLOAT_OOB_FILL_NONE);
}

}

extern "C" void kernel_launch(void* const* d_in, const int* in_sizes, int n_in, void* d_out, int out_size) {
  using namespace ssmffn;
  void* fn = nullptr;
  cudaDriverEntryPointQueryResult q;
  cudaGetDriverEntryPoint("cuTensorMapEncodeTiled", &fn, cudaEnableDefault, &q);
  EncodeFn enc = (EncodeFn)fn;
  Params P;
  {
    const cuuint64_t d3[3] = {64, 576, 72}, s3[2] = {4608 * 2, 128};
    const cuuint32_t b3[3] = {64, 32, 2};
    make_map(enc, &P.WgA, d_in[10], 3, d3, s3, b3);
    make_map(enc, &P.WuA, d_in[11], 3, d3, s3, b3);
    const cuuint64_t d2[2] = {4608, 576}, s2[1] = {4608 * 2};
    const cuuint32_t b2[2] = {64, 64};
    make_map(enc, &P.WgB, d_in[10], 2, d2, s2, b2);
    make_map(enc, &P.WuB, d_in[11], 2, d2, s2, b2);
    const cuuint64_t dq[2] = {576, 576}, sq[1] = {576 * 2};
    make_map(enc, &P.Bre, d_in[3], 2, dq, sq, b2);
    make_map(enc, &P.Bim, d_in[4], 2, dq, sq, b2);
    const cuuint32_t bc[2] = {64, 144};
    make_map(enc, &P.Cre, d_in[5], 2, dq, sq, bc);
    make_map(enc, &P.Cim, d_in[6], 2, dq, sq, bc);
    const cuuint64_t dx[5] = {576, 2, 4, 8, 32}, sx[4] = {1152, 16 * 1152, 2 * 1152, 64 * 1152};
    const cuuint32_t bx[5] = {64, 2, 4, 8, 1};
    make_map(enc, &P.X, d_in[0], 5, dx, sx, bx);
  }
  P.x = (const uint4*)d_in[0];
  P.lre = (const __nv_bfloat16*)d_in[1];
  P.lim = (const __nv_bfloat16*)d_in[2];
  P.ldt = (const __nv_bfloat16*)d_in[7];
  P.dskip = (const uint32_t*)d_in[8];
  P.wd = (const uint4*)d_in[12];
  P.out = (float*)d_out;
  cudaFuncSetAttribute(fused_kernel, cudaFuncAttributeMaxDynamicSharedMemorySize, SMEM_BYTES);
  fused_kernel<<<NCTA, 384, SMEM_BYTES, cudaStreamPerThread>>>(P);
}
```

```cpp
#include <cuda_runtime.h>
#include <cuda.h>
#include <cuda_bf16.h>
#include <stdint.h>

namespace ssmffn {

#define PACE 99
#define GATE 99
#define XL 0
#define LEAD1 2
#define LEAD2 2
#define NI 3
constexpr int NCTA = 128;
constexpr uint32_t OFF_RING = 131072, ST1 = 16384, NST1 = 6, OFF_RB = 147456, STB = 18432;
constexpr uint32_t OFF_DUMP = 94208, OFF_ZERO = 81920;
constexpr uint32_t OFF_R2 = 32768, ST2 = 25600, NST2 = 7;
constexpr uint32_t OFF_XT = OFF_R2 + NST2 * ST2;
constexpr uint32_t OFF_BAR = OFF_XT + 18432;
constexpr uint32_t B_FULL1 = 0, B_EMPTY1 = 48, B_FULL2 = 96, B_EMPTY2 = 152, B_FULLB = 208, B_EMPTYB = 240, B_X = 272,
                   B_DUMP = 344, B_SCAN = 352, B_STF = 360, B_STE = 376, B_XT = 392, B_GT = 400, B_STAT = 416, B_PUB = 424;
constexpr uint32_t OFF_STAT = OFF_BAR + 432;
constexpr uint32_t OFF_D = OFF_STAT + 512;
constexpr uint32_t SMEM_BYTES = OFF_D + 144;
constexpr uint32_t SPIN_LIMIT = 4000000;

struct Scratch {
  uint4 HS[16 * 18 * 1024];
  uint4 G[16 * 8 * 1152];
  uint4 E[16 * 576];
  uint4 S[16 * 64];
  uint32_t cntHS[16 * 32], cntG[32 * 32], epoch[NCTA * 32];
};
__device__ __align__(1024) Scratch g_scr;
#define TR(id)
#define TRG(id)
#define TRW(c, wq, id)

struct Params {
  CUtensorMap B[2], W[2], Wd, C[2], C8[2], X8, O, O8, X;
};

template<int TA, int TB> __device__ __forceinline__ void wgmma_ss64(float (&d)[32], uint32_t alo, uint32_t blo, int sd) {
  asm volatile("{\n.reg .pred p;\n.reg .b64 da, db;\nsetp.ne.b32 p, %35, 0;\nmov.b64 da, {%32, %34};\nmov.b64 db, {%33, %34};\n"
    "wgmma.mma_async.sync.aligned.m64n64k16.f32.bf16.bf16 {%0, %1, %2, %3, %4, %5, %6, %7, %8, %9, %10, %11, %12, %13, %14, %15, %16, %17, %18, %19, %20, %21, %22, %23, %24, %25, %26, %27, %28, %29, %30, %31}, da, db, p, 1, 1, %36, %37;\n}\n"
    : "+f"(d[0]), "+f"(d[1]), "+f"(d[2]), "+f"(d[3]), "+f"(d[4]), "+f"(d[5]), "+f"(d[6]), "+f"(d[7]), "+f"(d[8]), "+f"(d[9]), "+f"(d[10]), "+f"(d[11]), "+f"(d[12]), "+f"(d[13]), "+f"(d[14]), "+f"(d[15]), "+f"(d[16]), "+f"(d[17]), "+f"(d[18]), "+f"(d[19]), "+f"(d[20]), "+f"(d[21]), "+f"(d[22]), "+f"(d[23]), "+f"(d[24]), "+f"(d[25]), "+f"(d[26]), "+f"(d[27]), "+f"(d[28]), "+f"(d[29]), "+f"(d[30]), "+f"(d[31])
    : "r"(alo), "r"(blo), "r"(0x40000040u), "r"(sd), "n"(TA), "n"(TB));
}
template<int TB> __device__ __forceinline__ void wgmma_rs64(float (&d)[32], const uint32_t* a, uint32_t blo, int sd) {
  asm volatile("{\n.reg .pred p;\n.reg .b64 db;\nsetp.ne.b32 p, %38, 0;\nmov.b64 db, {%36, %37};\n"
    "wgmma.mma_async.sync.aligned.m64n64k16.f32.bf16.bf16 {%0, %1, %2, %3, %4, %5, %6, %7, %8, %9, %10, %11, %12, %13, %14, %15, %16, %17, %18, %19, %20, %21, %22, %23, %24, %25, %26, %27, %28, %29, %30, %31}, {%32, %33, %34, %35}, db, p, 1, 1, %39;\n}\n"
    : "+f"(d[0]), "+f"(d[1]), "+f"(d[2]), "+f"(d[3]), "+f"(d[4]), "+f"(d[5]), "+f"(d[6]), "+f"(d[7]), "+f"(d[8]), "+f"(d[9]), "+f"(d[10]), "+f"(d[11]), "+f"(d[12]), "+f"(d[13]), "+f"(d[14]), "+f"(d[15]), "+f"(d[16]), "+f"(d[17]), "+f"(d[18]), "+f"(d[19]), "+f"(d[20]), "+f"(d[21]), "+f"(d[22]), "+f"(d[23]), "+f"(d[24]), "+f"(d[25]), "+f"(d[26]), "+f"(d[27]), "+f"(d[28]), "+f"(d[29]), "+f"(d[30]), "+f"(d[31])
    : "r"(a[0]), "r"(a[1]), "r"(a[2]), "r"(a[3]), "r"(blo), "r"(0x40000040u), "r"(sd), "n"(TB));
}
template<int TA, int TB> __device__ __forceinline__ void wgmma_ss72(float (&d)[36], uint32_t alo, uint32_t blo, int sd) {
  asm volatile("{\n.reg .pred p;\n.reg .b64 da, db;\nsetp.ne.b32 p, %39, 0;\nmov.b64 da, {%36, %38};\nmov.b64 db, {%37, %38};\n"
    "wgmma.mma_async.sync.aligned.m64n72k16.f32.bf16.bf16 {%0, %1, %2, %3, %4, %5, %6, %7, %8, %9, %10, %11, %12, %13, %14, %15, %16, %17, %18, %19, %20, %21, %22, %23, %24, %25, %26, %27, %28, %29, %30, %31, %32, %33, %34, %35}, da, db, p, 1, 1, %40, %41;\n}\n"
    : "+f"(d[0]), "+f"(d[1]), "+f"(d[2]), "+f"(d[3]), "+f"(d[4]), "+f"(d[5]), "+f"(d[6]), "+f"(d[7]), "+f"(d[8]), "+f"(d[9]), "+f"(d[10]), "+f"(d[11]), "+f"(d[12]), "+f"(d[13]), "+f"(d[14]), "+f"(d[15]), "+f"(d[16]), "+f"(d[17]), "+f"(d[18]), "+f"(d[19]), "+f"(d[20]), "+f"(d[21]), "+f"(d[22]), "+f"(d[23]), "+f"(d[24]), "+f"(d[25]), "+f"(d[26]), "+f"(d[27]), "+f"(d[28]), "+f"(d[29]), "+f"(d[30]), "+f"(d[31]), "+f"(d[32]), "+f"(d[33]), "+f"(d[34]), "+f"(d[35])
    : "r"(alo), "r"(blo), "r"(0x40000040u), "r"(sd), "n"(TA), "n"(TB));
}
template<int TB> __device__ __forceinline__ void wgmma_rs72(float (&d)[36], const uint32_t* a, uint32_t blo, int sd) {
  asm volatile("{\n.reg .pred p;\n.reg .b64 db;\nsetp.ne.b32 p, %42, 0;\nmov.b64 db, {%40, %41};\n"
    "wgmma.mma_async.sync.aligned.m64n72k16.f32.bf16.bf16 {%0, %1, %2, %3, %4, %5, %6, %7, %8, %9, %10, %11, %12, %13, %14, %15, %16, %17, %18, %19, %20, %21, %22, %23, %24, %25, %26, %27, %28, %29, %30, %31, %32, %33, %34, %35}, {%36, %37, %38, %39}, db, p, 1, 1, %43;\n}\n"
    : "+f"(d[0]), "+f"(d[1]), "+f"(d[2]), "+f"(d[3]), "+f"(d[4]), "+f"(d[5]), "+f"(d[6]), "+f"(d[7]), "+f"(d[8]), "+f"(d[9]), "+f"(d[10]), "+f"(d[11]), "+f"(d[12]), "+f"(d[13]), "+f"(d[14]), "+f"(d[15]), "+f"(d[16]), "+f"(d[17]), "+f"(d[18]), "+f"(d[19]), "+f"(d[20]), "+f"(d[21]), "+f"(d[22]), "+f"(d[23]), "+f"(d[24]), "+f"(d[25]), "+f"(d[26]), "+f"(d[27]), "+f"(d[28]), "+f"(d[29]), "+f"(d[30]), "+f"(d[31]), "+f"(d[32]), "+f"(d[33]), "+f"(d[34]), "+f"(d[35])
    : "r"(a[0]), "r"(a[1]), "r"(a[2]), "r"(a[3]), "r"(blo), "r"(0x40000040u), "r"(sd), "n"(TB));
}

__device__ __forceinline__ uint32_t smem_u32(const void* p) { return (uint32_t)__cvta_generic_to_shared(p); }
__device__ __forceinline__ void mbar_init(uint32_t bar, uint32_t cnt) { asm volatile("mbarrier.init.shared::cta.b64 [%0], %1;" :: "r"(bar), "r"(cnt)); }
__device__ __forceinline__ void mbar_expect_tx(uint32_t bar, uint32_t bytes) { asm volatile("mbarrier.arrive.expect_tx.shared::cta.b64 _, [%0], %1;" :: "r"(bar), "r"(bytes) : "memory"); }
__device__ __forceinline__ void mbar_arrive(uint32_t bar) { asm volatile("mbarrier.arrive.shared::cta.b64 _, [%0];" :: "r"(bar) : "memory"); }
__device__ __forceinline__ void mbar_arrive_rem(uint32_t rbar) { asm volatile("mbarrier.arrive.shared::cluster.b64 _, [%0];" :: "r"(rbar) : "memory"); }
__device__ __forceinline__ void mbar_wait(uint32_t bar, uint32_t parity) {
  asm volatile("{\n.reg .pred p;\n.reg .u32 c;\n"
    "mbarrier.try_wait.parity.shared::cta.b64 p, [%0], %1;\n"
    "@p bra.uni DONE;\n"
    "mov.u32 c, 0;\n"
    "LOOP:\n"
    "mbarrier.try_wait.parity.shared::cta.b64 p, [%0], %1;\n"
    "@p bra.uni DONE;\n"
    "add.u32 c, c, 1;\n"
    "setp.lt.u32 p, c, %2;\n"
    "@p bra.uni LOOP;\n"
    "trap;\n"
    "DONE:\n}" :: "r"(bar), "r"(parity), "n"(SPIN_LIMIT) : "memory");
}
template<int SLEEP>
__device__ __forceinline__ uint32_t poll_ge(const uint32_t* p, uint32_t target) {
  uint32_t v;
  asm volatile("{\n.reg .pred p;\n.reg .u32 c;\n.reg .s32 d;\n"
    "mov.u32 c, 0;\n"
    "LOOP:\n"
    "ld.acquire.gpu.global.u32 %0, [%1];\n"
    "sub.s32 d, %0, %2;\n"
    "setp.ge.s32 p, d, 0;\n"
    "@p bra DONE;\n"
    "nanosleep.u32 %4;\n"
    "add.u32 c, c, 1;\n"
    "setp.lt.u32 p, c, %3;\n"
    "@p bra LOOP;\n"
    "trap;\n"
    "DONE:\n}" : "=&r"(v) : "l"(p), "r"(target), "n"(SPIN_LIMIT), "n"(SLEEP) : "memory");
  return v;
}
__device__ __forceinline__ void st_release(uint32_t* p, uint32_t v) { asm volatile("st.release.gpu.global.u32 [%0], %1;" :: "l"(p), "r"(v) : "memory"); }
__device__ __forceinline__ void red_release(uint32_t* p, uint32_t v) { asm volatile("red.release.gpu.global.add.u32 [%0], %1;" :: "l"(p), "r"(v) : "memory"); }
__device__ __forceinline__ uint32_t ld_relaxed(const uint32_t* p) { uint32_t v; asm volatile("ld.relaxed.gpu.global.u32 %0, [%1];" : "=r"(v) : "l"(p) : "memory"); return v; }
__device__ __forceinline__ void st_b128(uint4* p, uint32_t a, uint32_t b, uint32_t c, uint32_t d) {
  asm volatile("{\n.reg .b128 q;\n.reg .b64 l, h;\nmov.b64 l, {%1, %2};\nmov.b64 h, {%3, %4};\nmov.b128 q, {l, h};\nst.relaxed.gpu.global.b128 [%0], q;\n}"
    :: "l"(p), "r"(a), "r"(b), "r"(c), "r"(d) : "memory");
}
__device__ __forceinline__ uint4 ld_b128(const uint4* p) {
  uint4 v;
  asm volatile("{\n.reg .b128 q;\n.reg .b64 l, h;\nld.relaxed.gpu.global.b128 q, [%4];\nmov.b128 {l, h}, q;\nmov.b64 {%0, %1}, l;\nmov.b64 {%2, %3}, h;\n}"
    : "=r"(v.x), "=r"(v.y), "=r"(v.z), "=r"(v.w) : "l"(p) : "memory");
  return v;
}
__device__ __forceinline__ void st_b64(void* p, uint32_t a, uint32_t b) {
  asm volatile("{\n.reg .b64 l;\nmov.b64 l, {%1, %2};\nst.relaxed.gpu.global.b64 [%0], l;\n}" :: "l"(p), "r"(a), "r"(b) : "memory");
}
__device__ __forceinline__ uint4 ld_2xb64(const uint4* p) {
  uint4 v;
  asm volatile("{\n.reg .b64 l, h;\nld.relaxed.gpu.global.v2.b64 {l, h}, [%4];\nmov.b64 {%0, %1}, l;\nmov.b64 {%2, %3}, h;\n}"
    : "=r"(v.x), "=r"(v.y), "=r"(v.z), "=r"(v.w) : "l"(p) : "memory");
  return v;
}
__device__ __forceinline__ uint2 ldg_nc64(const void* p) { uint2 v; asm volatile("ld.global.nc.L1::no_allocate.v2.u32 {%0, %1}, [%2];" : "=r"(v.x), "=r"(v.y) : "l"(p)); return v; }
__device__ __forceinline__ bool elect_one() {
  uint32_t p; asm volatile("{\n.reg .pred P;\nelect.sync _|P, 0xffffffff;\nselp.u32 %0, 1, 0, P;\n}" : "=r"(p)); return p;
}
__device__ __forceinline__ void fence_async_global() { asm volatile("fence.proxy.async.global;" ::: "memory"); }
__device__ __forceinline__ void fence_async_smem() { asm volatile("fence.proxy.async.shared::cta;" ::: "memory"); }
#define POLMASK 7
template<int ID> __device__ __forceinline__ uint64_t policy_stream() {
  uint64_t p;
  if ((POLMASK >> ID) & 1) asm volatile("createpolicy.fractional.L2::evict_first.b64 %0, 1.0;" : "=l"(p));
  else asm volatile("createpolicy.fractional.L2::evict_normal.b64 %0, 1.0;" : "=l"(p));
  return p;
}
__device__ __forceinline__ void tma2d(uint32_t dst, const CUtensorMap* m, int c0, int c1, uint32_t bar, uint64_t pol) {
  asm volatile("cp.async.bulk.tensor.2d.shared::cluster.global.mbarrier::complete_tx::bytes.L2::cache_hint [%0], [%1, {%3, %4}], [%2], %5;"
    :: "r"(dst), "l"(m), "r"(bar), "r"(c0), "r"(c1), "l"(pol) : "memory");
}
__device__ __forceinline__ void tma3d(uint32_t dst, const CUtensorMap* m, int c0, int c1, int c2, uint32_t bar, uint64_t pol) {
  asm volatile("cp.async.bulk.tensor.3d.shared::cluster.global.mbarrier::complete_tx::bytes.L2::cache_hint [%0], [%1, {%3, %4, %5}], [%2], %6;"
    :: "r"(dst), "l"(m), "r"(bar), "r"(c0), "r"(c1), "r"(c2), "l"(pol) : "memory");
}
__device__ __forceinline__ void tma_x(uint32_t dst, const CUtensorMap* m, int c0, int c4, uint32_t bar) {
  asm volatile("cp.async.bulk.tensor.5d.shared::cluster.global.mbarrier::complete_tx::bytes [%0], [%1, {%3, %5, %5, %5, %4}], [%2];"
    :: "r"(dst), "l"(m), "r"(bar), "r"(c0), "r"(c4), "r"(0) : "memory");
}
__device__ __forceinline__ void bulk_ld(uint32_t dst, const void* src, uint32_t bytes, uint32_t bar, uint64_t pol) {
  asm volatile("cp.async.bulk.shared::cluster.global.mbarrier::complete_tx::bytes.L2::cache_hint [%0], [%1], %2, [%3], %4;"
    :: "r"(dst), "l"(src), "r"(bytes), "r"(bar), "l"(pol) : "memory");
}
__device__ __forceinline__ void bulk_ld_mc(uint32_t dst, const void* src, uint32_t bytes, uint32_t bar, uint64_t pol) {
  asm volatile("cp.async.bulk.shared::cluster.global.mbarrier::complete_tx::bytes.multicast::cluster.L2::cache_hint [%0], [%1], %2, [%3], %4, %5;"
    :: "r"(dst), "l"(src), "r"(bytes), "r"(bar), "h"((uint16_t)3), "l"(pol) : "memory");
}
__device__ __forceinline__ void prefetch_map(const CUtensorMap* m) { asm volatile("prefetch.tensormap [%0];" :: "l"(m) : "memory"); }
__device__ __forceinline__ void wg_fence() { asm volatile("wgmma.fence.sync.aligned;" ::: "memory"); }
__device__ __forceinline__ void wg_commit() { asm volatile("wgmma.commit_group.sync.aligned;" ::: "memory"); }
template<int N> __device__ __forceinline__ void wg_wait() { asm volatile("wgmma.wait_group.sync.aligned %0;" :: "n"(N) : "memory"); }
template<int N> __device__ __forceinline__ void zero(float (&d)[N]) {
  #pragma unroll
  for (int i = 0; i < N; i++) d[i] = 0.f;
}
template<int N> __device__ __forceinline__ void pin(float (&d)[N]) {
  #pragma unroll
  for (int i = 0; i < N; i++) asm volatile("" : "+f"(d[i]) :: "memory");
}
__device__ __forceinline__ void cluster_arrive() { asm volatile("barrier.cluster.arrive.relaxed.aligned;" ::: "memory"); }
__device__ __forceinline__ void cluster_wait() { asm volatile("barrier.cluster.wait.acquire.aligned;" ::: "memory"); }
__device__ __forceinline__ void bar_sync(int id, int n) { asm volatile("bar.sync %0, %1;" :: "r"(id), "r"(n) : "memory"); }
template<int R> __device__ __forceinline__ void reg_alloc() { asm volatile("setmaxnreg.inc.sync.aligned.u32 %0;" :: "n"(R)); }
template<int R> __device__ __forceinline__ void reg_dealloc() { asm volatile("setmaxnreg.dec.sync.aligned.u32 %0;" :: "n"(R)); }

__device__ __forceinline__ uint4 ldg_nc(const uint4* p, uint64_t pol) {
  uint4 v; asm volatile("ld.global.nc.L1::no_allocate.L2::cache_hint.v4.u32 {%0, %1, %2, %3}, [%4], %5;" : "=r"(v.x), "=r"(v.y), "=r"(v.z), "=r"(v.w) : "l"(p), "l"(pol)); return v;
}
__device__ __forceinline__ uint4 lds128(uint32_t a) {
  uint4 v; asm volatile("ld.shared.v4.u32 {%0, %1, %2, %3}, [%4];" : "=r"(v.x), "=r"(v.y), "=r"(v.z), "=r"(v.w) : "r"(a) : "memory"); return v;
}
__device__ __forceinline__ uint32_t ldg_nc32(const void* p) { uint32_t v; asm volatile("ld.global.nc.u32 %0, [%1];" : "=r"(v) : "l"(p)); return v; }
__device__ __forceinline__ float4 ldg_cg(const float4* p) {
  float4 v; asm volatile("ld.global.cg.v4.f32 {%0, %1, %2, %3}, [%4];" : "=f"(v.x), "=f"(v.y), "=f"(v.z), "=f"(v.w) : "l"(p) : "memory"); return v;
}
__device__ __forceinline__ void stg128(void* p, uint32_t a, uint32_t b, uint32_t c, uint32_t d) {
  asm volatile("st.global.v4.u32 [%0], {%1, %2, %3, %4};" :: "l"(p), "r"(a), "r"(b), "r"(c), "r"(d) : "memory");
}
__device__ __forceinline__ void stg128f(void* p, float a, float b, float c, float d) {
  asm volatile("st.global.v4.f32 [%0], {%1, %2, %3, %4};" :: "l"(p), "f"(a), "f"(b), "f"(c), "f"(d) : "memory");
}
__device__ __forceinline__ void sts128(uint32_t a, uint32_t x, uint32_t y, uint32_t z, uint32_t w) {
  asm volatile("st.shared.v4.u32 [%0], {%1, %2, %3, %4};" :: "r"(a), "r"(x), "r"(y), "r"(z), "r"(w) : "memory");
}
__device__ __forceinline__ void sts64f(uint32_t a, float x, float y) { asm volatile("st.shared.v2.f32 [%0], {%1, %2};" :: "r"(a), "f"(x), "f"(y) : "memory"); }
__device__ __forceinline__ float2 lds64f(uint32_t a) { float2 v; asm volatile("ld.shared.v2.f32 {%0, %1}, [%2];" : "=f"(v.x), "=f"(v.y) : "r"(a) : "memory"); return v; }
__device__ __forceinline__ uint32_t lds32(uint32_t a) { uint32_t v; asm volatile("ld.shared.u32 %0, [%1];" : "=r"(v) : "r"(a) : "memory"); return v; }
__device__ __forceinline__ uint32_t pack_bf16(float lo, float hi) { uint32_t r; asm("cvt.rn.bf16x2.f32 %0, %1, %2;" : "=r"(r) : "f"(hi), "f"(lo)); return r; }
__device__ __forceinline__ uint32_t bmul2(uint32_t a, uint32_t b) { uint32_t r; asm("mul.rn.bf16x2 %0, %1, %2;" : "=r"(r) : "r"(a), "r"(b)); return r; }
__device__ __forceinline__ uint32_t bsub2(uint32_t a, uint32_t b) { uint32_t r; asm("sub.rn.bf16x2 %0, %1, %2;" : "=r"(r) : "r"(a), "r"(b)); return r; }
__device__ __forceinline__ uint32_t bfma2(uint32_t a, uint32_t b, uint32_t c) { uint32_t r; asm("fma.rn.bf16x2 %0, %1, %2, %3;" : "=r"(r) : "r"(a), "r"(b), "r"(c)); return r; }
__device__ __forceinline__ float bf_lo(uint32_t v) { return __uint_as_float(v << 16); }
__device__ __forceinline__ float bf_hi(uint32_t v) { return __uint_as_float(v & 0xffff0000u); }
__device__ __forceinline__ float bf_round(float v) { return bf_lo(pack_bf16(v, 0.f)); }
__device__ __forceinline__ float rcp_fast(float v) { float r; asm("rcp.approx.ftz.f32 %0, %1;" : "=f"(r) : "f"(v)); return r; }
__device__ __forceinline__ void mma_stat(float (&d)[4], uint32_t a, uint32_t b) {
  asm volatile("mma.sync.aligned.m16n8k16.row.col.f32.bf16.bf16.f32 {%0, %1, %2, %3}, {%4, %6, %5, %6}, {%4, %5}, {%0, %1, %2, %3};"
    : "+f"(d[0]), "+f"(d[1]), "+f"(d[2]), "+f"(d[3]) : "r"(a), "r"(b), "r"(0x3F803F80u));
}
__device__ __forceinline__ float2 cmul(float2 a, float2 b) { return make_float2(fmaf(a.x, b.x, -a.y * b.y), fmaf(a.x, b.y, a.y * b.x)); }
__device__ __forceinline__ float2 cfma(float2 a, float2 b, float2 c) { return make_float2(fmaf(a.x, b.x, fmaf(-a.y, b.y, c.x)), fmaf(a.x, b.y, fmaf(a.y, b.x, c.y))); }

__device__ __forceinline__ void ln_consts(uint32_t st, uint32_t& m2, uint32_t& rh2, uint32_t& rl2) {
  m2 = __byte_perm(st, st, 0x1010);
  float r; asm("rcp.approx.ftz.f32 %0, %1;" : "=f"(r) : "f"(bf_hi(st)));
  float rh = bf_round(r);
  rh2 = pack_bf16(rh, rh);
  rl2 = pack_bf16(r - rh, r - rh);
}
__device__ __forceinline__ uint32_t ln_apply(uint32_t x2, uint32_t m2, uint32_t rh2, uint32_t rl2) {
  uint32_t d = bsub2(x2, m2);
  return bfma2(d, rh2, bmul2(d, rl2));
}

__device__ __forceinline__ void tma2d_mc(uint32_t dst, const CUtensorMap* m, int c0, int c1, uint32_t bar, uint64_t pol) {
  asm volatile("cp.async.bulk.tensor.2d.shared::cluster.global.mbarrier::complete_tx::bytes.multicast::cluster.L2::cache_hint [%0], [%1, {%3, %4}], [%2], %5, %6;"
    :: "r"(dst), "l"(m), "r"(bar), "r"(c0), "r"(c1), "h"((uint16_t)3), "l"(pol) : "memory");
}
__device__ __forceinline__ void tma2d_st(const CUtensorMap* m, int c0, int c1, uint32_t src) {
  asm volatile("cp.async.bulk.tensor.2d.global.shared::cta.bulk_group [%0, {%2, %3}], [%1];" :: "l"(m), "r"(src), "r"(c0), "r"(c1) : "memory");
}
__device__ __forceinline__ void bulk_red(void* dst, uint32_t src, uint32_t bytes) {
  asm volatile("cp.reduce.async.bulk.global.shared::cta.bulk_group.add.noftz.bf16 [%0], [%1], %2;" :: "l"(dst), "r"(src), "r"(bytes) : "memory");
}
__device__ __forceinline__ void bulk_st(void* dst, uint32_t src, uint32_t bytes) {
  asm volatile("cp.async.bulk.global.shared::cta.bulk_group [%0], [%1], %2;" :: "l"(dst), "r"(src), "r"(bytes) : "memory");
}
__device__ __forceinline__ void red_relaxed(uint32_t* p, uint32_t v) { asm volatile("red.relaxed.gpu.global.add.u32 [%0], %1;" :: "l"(p), "r"(v) : "memory"); }
__device__ __forceinline__ void bar_arrive(int id, int n) { asm volatile("bar.arrive %0, %1;" :: "r"(id), "r"(n) : "memory"); }
__device__ __forceinline__ void bulk_commit() { asm volatile("cp.async.bulk.commit_group;" ::: "memory"); }
__device__ __forceinline__ void bulk_wait_read() { asm volatile("cp.async.bulk.wait_group.read 0;" ::: "memory"); }
__device__ __forceinline__ void bulk_wait() { asm volatile("cp.async.bulk.wait_group 0;" ::: "memory"); }
__device__ __forceinline__ void ldsm4(uint32_t* r, uint32_t a) {
  asm volatile("ldmatrix.sync.aligned.m8n8.x4.shared.b16 {%0, %1, %2, %3}, [%4];" : "=r"(r[0]), "=r"(r[1]), "=r"(r[2]), "=r"(r[3]) : "r"(a) : "memory");
}
__device__ __forceinline__ void ldsm2(uint32_t* r, uint32_t a) {
  asm volatile("ldmatrix.sync.aligned.m8n8.x2.shared.b16 {%0, %1}, [%2];" : "=r"(r[0]), "=r"(r[1]) : "r"(a) : "memory");
}
__device__ __forceinline__ void stsm4(uint32_t a, uint32_t x, uint32_t y, uint32_t z, uint32_t w) {
  asm volatile("stmatrix.sync.aligned.m8n8.x4.shared.b16 [%0], {%1, %2, %3, %4};" :: "r"(a), "r"(x), "r"(y), "r"(z), "r"(w) : "memory");
}
__device__ __forceinline__ void stsm4t(uint32_t a, uint32_t x, uint32_t y, uint32_t z, uint32_t w) {
  asm volatile("stmatrix.sync.aligned.m8n8.x4.trans.shared.b16 [%0], {%1, %2, %3, %4};" :: "r"(a), "r"(x), "r"(y), "r"(z), "r"(w) : "memory");
}
__device__ __forceinline__ void stsm2t(uint32_t a, uint32_t x, uint32_t y) {
  asm volatile("stmatrix.sync.aligned.m8n8.x2.trans.shared.b16 [%0], {%1, %2};" :: "r"(a), "r"(x), "r"(y) : "memory");
}
__device__ __forceinline__ void mov_tied(uint32_t* r, const uint32_t* v, uint32_t a) {
  asm volatile("{\n.reg .pred p;\nsetp.ne.u32 p, %8, 0;\n@p mov.b32 %0, %4;\n@p mov.b32 %1, %5;\n@p mov.b32 %2, %6;\n@p mov.b32 %3, %7;\n}"
    : "+r"(r[0]), "+r"(r[1]), "+r"(r[2]), "+r"(r[3]) : "r"(v[0]), "r"(v[1]), "r"(v[2]), "r"(v[3]), "r"(a));
}
__device__ __forceinline__ void lds128_tied(uint32_t* r, uint32_t a) {
  asm volatile("{\n.reg .pred p;\nsetp.ne.u32 p, %4, 0;\n@p ld.shared.v4.u32 {%0, %1, %2, %3}, [%4];\n}" : "+r"(r[0]), "+r"(r[1]), "+r"(r[2]), "+r"(r[3]) : "r"(a) : "memory");
}
__device__ __forceinline__ void sts32(uint32_t a, uint32_t v) { asm volatile("st.shared.u32 [%0], %1;" :: "r"(a), "r"(v) : "memory"); }
__device__ __forceinline__ float2 lds_u(uint32_t a) { return make_float2(__uint_as_float(lds32(a)), __uint_as_float(lds32(a + 36864))); }
__device__ __forceinline__ void sts128f(uint32_t a, float x, float y, float z, float w) {
  asm volatile("st.shared.v4.f32 [%0], {%1, %2, %3, %4};" :: "r"(a), "f"(x), "f"(y), "f"(z), "f"(w) : "memory");
}

template<uint32_t FULL, uint32_t EMPTY, uint32_t N, uint32_t SZ>
struct Ring {
  uint32_t st, ph, prev;
  __device__ __forceinline__ void init() { st = 0; ph = 0; prev = 0; }
  __device__ __forceinline__ void wait(uint32_t bars) const { mbar_wait(bars + FULL + 8 * st, ph); }
  __device__ __forceinline__ uint32_t soff() const { return st * (SZ / 16); }
  __device__ __forceinline__ void next() {
    prev = EMPTY + 8 * st;
    if (++st == N) { st = 0; ph ^= 1; }
  }
};
typedef Ring<B_FULL1, B_EMPTY1, NST1, ST1> Ring1;
typedef Ring<B_FULL2, B_EMPTY2, NST2, ST2> Ring2;

struct LnC { uint32_t m2[2], rh2[2], rl2[2]; };
__device__ __forceinline__ void ln_block(const LnC& lc, uint32_t* a) {
  #pragma unroll
  for (int i = 0; i < 16; i++) a[i] = ln_apply(a[i], lc.m2[i & 1], lc.rh2[i & 1], lc.rl2[i & 1]);
}
__device__ __forceinline__ uint32_t h_pair(const uint32_t (&pg)[16], const float (&U)[32], int i) {
  return bmul2(pg[i], pack_bf16(U[2 * i], U[2 * i + 1]));
}

__global__ void __cluster_dims__(2, 1, 1) __launch_bounds__(384, 1) fused_kernel(Scratch* sc, const uint8_t* px, const __nv_bfloat16* plre,
    const __nv_bfloat16* plim, const __nv_bfloat16* pldt, const uint32_t* pdskip, const __grid_constant__ Params P) {
  extern __shared__ __align__(1024) uint8_t smem_raw[];
  const uint32_t sb = smem_u32(smem_raw);
  const uint32_t bars = sb + OFF_BAR;
  const int b = blockIdx.x;
  const int wid = __shfl_sync(0xffffffffu, threadIdx.x >> 5, 0);
  const int lane = threadIdx.x & 31;
  const int rank = b & 1, j = (b >> 1) & 7, m = (b >> 4) * 2 + rank;
  TR(0); TRG(30);
  if (wid >= 8) {
    TR(8);
    reg_dealloc<40>();
    if (elect_one()) {
      if (wid == 8) {
        if (sb & 1023) asm volatile("trap;");
        #pragma unroll
        for (int i = 0; i < 9; i++) mbar_init(bars + B_X + 8 * i, 1);
      } else if (wid == 9) {
        #pragma unroll
        for (int i = 0; i < 4; i++) { mbar_init(bars + B_FULLB + 8 * i, 1); mbar_init(bars + B_EMPTYB + 8 * i, 4); }
        mbar_init(bars + B_DUMP, 8); mbar_init(bars + B_STAT, 8); mbar_init(bars + B_PUB, 8); mbar_init(bars + B_SCAN, 3); mbar_init(bars + B_XT, 1);
        #pragma unroll
        for (int i = 0; i < 2; i++) { mbar_init(bars + B_STF + 8 * i, 4); mbar_init(bars + B_STE + 8 * i, 1); mbar_init(bars + B_GT + 8 * i, 1); }
      } else if (wid == 10) {
        #pragma unroll
        for (int i = 0; i < NST2; i++) { mbar_init(bars + B_FULL2 + 8 * i, 1); mbar_init(bars + B_EMPTY2 + 8 * i, 4); }
      } else {
        #pragma unroll
        for (int i = 0; i < NST1; i++) { mbar_init(bars + B_FULL1 + 8 * i, 1); mbar_init(bars + B_EMPTY1 + 8 * i, 4); }
      }
      asm volatile("fence.mbarrier_init.release.cluster;" ::: "memory");
      fence_async_smem();
    }
    __syncwarp();
    cluster_arrive();
    if (wid == 8) {
      const uint64_t pn = policy_stream<3>();
      auto ld_x = [&](int kb) {
        mbar_expect_tx(bars + B_X + 8 * kb, 16384);
        tma2d(sb + (8 - kb) * 16384, &P.X, kb * 64, m * 128, bars + B_X + 8 * kb, pn);
      };
      if (elect_one()) { ld_x(0); prefetch_map(&P.B[rank]); ld_x(8); }
      __syncwarp();
      TR(3);
      cluster_wait();
      TR(4);
      if (elect_one()) {
        const uint64_t pol = policy_stream<0>();
#pragma unroll 1
        for (int s = 0; s < 9; s++) {
          const uint32_t sl = (s + 3) & 3, fb = bars + B_FULLB + 8 * sl;
          if (s == PACE) mbar_wait(bars + B_PUB, 0);
          if (s == GATE) mbar_wait(bars + B_STAT, 0);
          if (s == 4) {
#pragma unroll 1
            for (int i = 0; i < 12; i++) prefetch_map(&P.B[0] + i);
          }
          if (s >= 4) mbar_wait(bars + B_EMPTYB + 8 * sl, s >> 3);
          mbar_expect_tx(fb, STB);
          const int kb = s < 7 ? (s < 2 ? s * 8 : s - 1) : 6 + rank;
          tma2d_mc(sb + OFF_RB + sl * STB + rank * 9216, &P.B[s < 7 ? rank : 8 - s], kb * 64, j * 72, fb, pol);
          if (s >= XL && s < 7) ld_x(s + 1 - XL);
          if (XL == 1 && s == 6) ld_x(7);
        }
        TR(5);
        const uint32_t tag = ld_relaxed(sc->epoch + b * 32) + 1;
        uint32_t st = 0, ph = 1;
#pragma unroll 1
        for (int t = 0; t < 9; t++) {
          if (t == 8) { poll_ge<100>(sc->cntHS + m * 32, tag * 24); fence_async_global(); }
#pragma unroll 1
          for (int s = 0; s < 9; s++) {
            const uint32_t fb = bars + B_FULL1 + 8 * st;
            if (t == 0 && s >= 1 && s < 5) mbar_wait(bars + B_EMPTYB + 8 * (s - 1), s != 4);
            mbar_wait(bars + B_EMPTY1 + 8 * st, ph);
            mbar_expect_tx(fb, ST1);
            const int a = (t < 8 || (s & 7) == 0) ? 2 * s + rank : s + 1 + 7 * rank;
            tma2d_mc(sb + OFF_RING + st * ST1 + rank * 8192, &P.W[a >= 9], (j * 9 + (t == 0 ? 6 : t < 7 ? t - 1 : t)) * 64, (a >= 9 ? a - 9 : a) * 64, fb, pol);
            if (++st == NST1) { st = 0; ph ^= 1; }
          }
        }
        TR(1);
        st = 0; ph = 0;
        int a = j + 1, si = 0;
#pragma unroll 1
        for (int i = 0; i < 45; i++) {
          const int gi = i < 36 ? (i & 3) : 3;
          const uint32_t fb = bars + B_FULL2 + 8 * st, dst = sb + OFF_R2 + st * ST2;
          mbar_wait(bars + B_EMPTY2 + 8 * st, ph);
          if (gi < 3) {
            mbar_expect_tx(fb, 24576);
            tma2d_mc(dst + rank * 12288, &P.Wd, a * 64, j * 576 + gi * 192 + rank * 96, fb, pol);
            if (gi == 2 && ++a == 9) a = 0;
          } else {
            mbar_expect_tx(fb, ST2);
            bulk_ld(dst, (const uint8_t*)sc->HS + (size_t)(m * 36 + si) * 8192, 8192, fb, pol);
            bulk_ld(dst + 8192, (const uint8_t*)sc->HS + (size_t)(m * 36 + 18 + si) * 8192, 8192, fb, pol);
            if ((si & 1) == rank) tma2d_mc(dst + 16384, &P.C[si >= 9], (si >= 9 ? si - 9 : si) * 64, j * 64, fb, pol);
            else tma2d_mc(dst + 24576, &P.C8[si >= 9], (si >= 9 ? si - 9 : si) * 64, 512 + j * 8, fb, pol);
            si++;
          }
          if (i == NST2 - 1) {
            mbar_expect_tx(bars + B_XT, 18432);
            tma2d(sb + OFF_XT, &P.X, j * 64, m * 128, bars + B_XT, pol);
            tma2d(sb + OFF_XT + 16384, &P.X8, 512 + j * 8, m * 128, bars + B_XT, pol);
          }
          if (++st == NST2) { st = 0; ph ^= 1; }
        }
        TR(2);
      }
    } else {
      const uint32_t tag = ld_relaxed(sc->epoch + b * 32) + 1;
      const int pl = (wid - 9) * 24 + min(lane, 23), p = j * 72 + pl;
      if (pl < 36) asm volatile("st.shared.u32 [%0], %1;" :: "r"(sb + OFF_D + pl * 4), "r"(ldg_nc32(pdskip + (pl < 32 ? j * 32 + pl : 224 + j * 4 + pl))) : "memory");
      const float lre = __bfloat162float(plre[p]), lim = __bfloat162float(plim[p]);
      const float dt = bf_round(expf(__bfloat162float(pldt[p])));
      const float er = expf(dt * lre);
      float sn, cs;
      sincosf(dt * lim, &sn, &cs);
      const float2 lam = make_float2(er * cs, er * sn);
      const float nr = lam.x - 1.0f, ni = lam.y, den = 2.0f / (lre * lre + lim * lim);
      const float2 cf = make_float2((nr * lre + ni * lim) * den, (ni * lre - nr * lim) * den);
      cluster_wait();
      const uint32_t ua = sb + OFF_DUMP + pl * 128 + ((pl & 7) << 4);
      float2 l128 = lam;
      #pragma unroll
      for (int i = 0; i < 7; i++) l128 = cmul(l128, l128);
      mbar_wait(bars + B_DUMP, 0);
      TR(1);
      {
        const uint32_t stg = sb + OFF_ZERO + (wid - 9) * 3072;
        #pragma unroll
        for (int i = 0; i < 6; i++) sts128(stg + i * 512 + lane * 16, 0, 0, 0, 0);
        fence_async_smem();
        __syncwarp();
        if (lane == 0) {
          uint8_t* z = (uint8_t*)sc->G + (size_t)(m * 8 + j) * 18432 + (wid - 9) * 6144;
          bulk_st(z, stg, 3072); bulk_st(z + 3072, stg, 3072); bulk_commit();
        }
      }
      if (lane < 24) {
        float2 cy = make_float2(0.f, 0.f);
        uint4 nr = lds128(ua), ni = lds128(ua + 9216);
#pragma unroll 2
        for (int ch = 1; ch <= 16; ch++) {
          const uint32_t re[4] = {nr.x, nr.y, nr.z, nr.w}, im[4] = {ni.x, ni.y, ni.z, ni.w};
          const uint32_t u = (ua ^ ((ch & 7) << 4)) + (ch & 8) * 2304;
          nr = lds128(u); ni = lds128(u + 9216);
          #pragma unroll
          for (int q = 0; q < 4; q++) {
            cy = cfma(lam, cy, make_float2(bf_lo(re[q]), bf_lo(im[q])));
            cy = cfma(lam, cy, make_float2(bf_hi(re[q]), bf_hi(im[q])));
          }
        }
        st_b128(sc->E + m * 576 + p, __float_as_uint(cy.x), __float_as_uint(cy.y), tag, tag);
        TR(2);
        cy = make_float2(0.f, 0.f);
#pragma unroll 1
        for (int i0 = 0; i0 < m; i0 += 3) {
          uint4 q[3];
          for (uint32_t spin = 0;; spin++) {
            #pragma unroll
            for (int i = 0; i < 3; i++) q[i] = ld_b128(sc->E + (i0 + i) * 576 + p);
            if (q[0].z == tag && q[1].z == tag && q[2].z == tag) break;
            if (spin > SPIN_LIMIT) asm volatile("trap;");
          }
          #pragma unroll
          for (int i = 0; i < 3; i++)
            if (i0 + i < m) cy = cfma(l128, cy, make_float2(__uint_as_float(q[i].x), __uint_as_float(q[i].y)));
        }
        TR(3);
        nr = lds128(ua); ni = lds128(ua + 9216);
        cy = cmul(cf, cy);
        cy.y = -cy.y;
        auto step = [&](float ur, float ui) {
          const float tx = __fmaf_rn(lam.y, cy.y, __fmul_rn(lam.x, cy.x)), ty = __fmaf_rn(-lam.y, cy.x, __fmul_rn(lam.x, cy.y));
          cy.x = __fmaf_rn(-cf.y, ui, __fmaf_rn(cf.x, ur, tx));
          cy.y = __fmaf_rn(-cf.y, ur, __fmaf_rn(-cf.x, ui, ty));
        };
#pragma unroll 2
        for (int ch = 1; ch <= 16; ch++) {
          uint32_t re[4] = {nr.x, nr.y, nr.z, nr.w}, im[4] = {ni.x, ni.y, ni.z, ni.w};
          const uint32_t u = (ua ^ ((ch & 7) << 4)) + (ch & 8) * 2304;
          nr = lds128(u); ni = lds128(u + 9216);
          #pragma unroll
          for (int q = 0; q < 4; q++) {
            step(bf_lo(re[q]), bf_lo(im[q]));
            const float2 a = cy;
            step(bf_hi(re[q]), bf_hi(im[q]));
            re[q] = pack_bf16(a.x, cy.x);
            im[q] = pack_bf16(a.y, cy.y);
          }
          const uint32_t o = (ua ^ (((ch - 1) & 7) << 4)) + ((ch - 1) & 8) * 2304;
          sts128(o, re[0], re[1], re[2], re[3]);
          sts128(o + 9216, im[0], im[1], im[2], im[3]);
        }
      }
      fence_async_smem();
      __syncwarp();
      if (lane == 0) {
        uint8_t* hs = (uint8_t*)sc->HS + (size_t)m * 294912 + p * 128;
        #pragma unroll
        for (int i = 0; i < 4; i++) bulk_st(hs + i * 73728, ua + i * 9216, 3072);
        bulk_commit();
        bulk_wait_read();
        mbar_arrive(bars + B_SCAN);
        bulk_wait();
        red_relaxed(sc->cntHS + m * 32, 1);
      }
      TR(4);
      if (wid < 11) {
        const int w = wid - 9;
        if (lane == 0) poll_ge<200>(sc->cntHS + m * 32, tag * 24);
        __syncwarp();
        fence_async_global();
        uint8_t* gp = (uint8_t*)sc->G + (size_t)(m * 8 + w * 4 + (lane & 3)) * 18432;
        int a = j + 1;
#pragma unroll 1
        for (int t = 0; t < 8; t++) {
          mbar_wait(bars + B_STF + 8 * w, t & 1);
          if (lane < 4) {
            bulk_red(gp + a * 2048, sb + 16384 + w * 8192 + lane * 2048, 2048);
            bulk_commit();
            if (t < 7) bulk_wait_read(); else bulk_wait();
          }
          __syncwarp();
          if (lane == 0) mbar_arrive(bars + B_STE + 8 * w);
          if (++a == 9) a = 0;
        }
        TR(5);
        if (lane == 0) {
          red_relaxed(sc->cntG + (m * 2 + w) * 32, 1);
          TR(6);
          poll_ge<20>(sc->cntG + (m * 2 + w) * 32, tag * 8);
          mbar_expect_tx(bars + B_GT + 8 * w, 9216);
        }
        __syncwarp();
        TR(7);
        fence_async_global();
        if (lane < 4) bulk_ld(sb + 16384 + w * 8192 + lane * 2048, gp + j * 2048, 2048, bars + B_GT + 8 * w, policy_stream<0>());
        __syncwarp();
        mbar_wait(bars + B_STF + 8 * w, 0);
        if (lane < 4) bulk_ld(sb + w * 8192 + 6144 + lane * 256, gp + 16384 + j * 256, 256, bars + B_GT + 8 * w, policy_stream<0>());
      }
    }
  } else {
    cluster_arrive();
    const int w = wid >> 2, warp = wid & 3, g = lane >> 2, c = lane & 3;
    const uint32_t lma = sb + w * 8192 + (warp * 16 + (lane & 15)) * 128 + (((lane >> 4) ^ (lane & 7)) << 4);
    uint32_t A[128], T[16];
    auto ld_x = [&](uint32_t* a, int kb) {
      #pragma unroll
      for (int k = 0; k < 4; k++) ldsm4(a + k * 4, (lma ^ (k << 5)) + (8 - kb) * 16384);
    };
    uint4 sv;
    {
      uint2 xr[9];
      const uint8_t* xp = px + (size_t)(m * 128 + j * 16 + wid + (lane >> 4) * 8) * 1152 + (lane & 15) * 8;
      #pragma unroll
      for (int i = 0; i < 9; i++) xr[i] = ldg_nc64(xp + i * 128);
      const uint32_t tag = ld_relaxed(sc->epoch + b * 32) + 1;
      const uint4* sp = sc->S + (m * 8 + wid) * 8 + g;
      sv = ld_2xb64(sp);
      reg_alloc<232>();
      float d[3][4];
      #pragma unroll
      for (int i = 0; i < 12; i++) d[i >> 2][i & 3] = 0.f;
      #pragma unroll
      for (int i = 0; i < 9; i++) mma_stat(d[i % 3], xr[i].x, xr[i].y);
      float sm = (d[0][2] + d[0][3]) + (d[1][2] + d[1][3]) + (d[2][2] + d[2][3]);
      float sq = (g & 1) ? d[0][1] + d[1][1] + d[2][1] : d[0][0] + d[1][0] + d[2][0];
      if (c != (g >> 1)) sq = 0.f;
      sm += __shfl_xor_sync(0xffffffffu, sm, 1);
      sq += __shfl_xor_sync(0xffffffffu, sq, 1);
      sq += __shfl_xor_sync(0xffffffffu, sq, 4);
      sq += __shfl_xor_sync(0xffffffffu, sq, 8);
      const float mean = sm * (1.0f / 576.0f);
      const float var = fmaxf(fmaf(-mean, mean, sq * (1.0f / 576.0f)), 0.f);
      float sd; asm("sqrt.approx.ftz.f32 %0, %1;" : "=f"(sd) : "f"(bf_round(bf_round(var) + 1e-5f)));
      if (lane == 0 || lane == 18) st_b64((uint8_t*)(sc->S + (m * 8 + j) * 8 + wid) + (lane >> 4) * 8, pack_bf16(mean, sd), tag);
      TR(20);
      cluster_wait();
      if (lane == 0) mbar_arrive(bars + B_PUB);
      sv = ld_2xb64(sp);
      mbar_wait(bars + B_X, 0);
      mbar_wait(bars + B_X + 64, 0);
      ld_x(A, 0);
      ld_x(T, 8);
      TR(1);
      for (uint32_t spin = 0; !__all_sync(0xffffffffu, sv.y == tag && sv.w == tag); spin++) {
        if (spin > SPIN_LIMIT) asm volatile("trap;");
        sv = ld_2xb64(sp);
      }
      TR(21);
      if (lane == 0) mbar_arrive(bars + B_STAT);
    }
    const bool elected = (threadIdx.x & 126) == 0;
    uint32_t rbar;
    asm("mapa.shared::cluster.u32 %0, %1, %2;" : "=r"(rbar) : "r"(bars), "r"(lane & 1));
    auto rel = [&](uint32_t off) { if (elected) mbar_arrive_rem(rbar + off); };
    const uint32_t sd16 = (sb & 0x3FFFF) >> 4;
    const uint32_t la8 = (sd16 + w * 512) | (1u << 16);
    float XG[32], XU[32];
    Ring1 rg; rg.init();
    int tt = 0;
    auto stage = [&](int s, bool last) {
      const uint32_t lb = (sd16 + (OFF_RING >> 4)) | (1u << 16);
      TRW(6, 1, 20 + (s + 8) % 9);
      rg.wait(bars);
      TRW(6, 2, 20 + (s + 8) % 9);
      wg_fence();
      #pragma unroll
      for (int i = 0; i < 2; i++) {
        const int a = (!last || s == 8) ? 2 * s + i : s + 1 + 7 * i, kb = a % 9;
        #pragma unroll
        for (int k = 0; k < 4; k++) {
          const uint32_t bd = lb + rg.soff() + i * 512 + k * 128;
          if (kb < 8) wgmma_rs64<1>(a < 9 ? XG : XU, &A[kb * 16 + k * 4], bd, (kb | k) != 0);
          else wgmma_ss64<0, 1>(a < 9 ? XG : XU, la8 + k * 2, bd, 1);
        }
      }
      wg_commit();
    };
    {
      if (c == 0) { sts32(sb + OFF_STAT + (wid * 16 + g) * 4, sv.x); sts32(sb + OFF_STAT + (wid * 16 + g + 8) * 4, sv.z); }
      const uint32_t m2[2] = {__byte_perm(sv.x, sv.x, 0x1010), __byte_perm(sv.z, sv.z, 0x1010)};
      float UR[36], UI[36];
      zero(UR); zero(UI);
      const uint32_t lb = (sd16 + (OFF_RB >> 4)) | (1u << 16);
      const uint32_t da = sb + OFF_DUMP + w * 18432 + ((lane >> 4) * 8 + (lane & 7)) * 128 + (((warp * 2 + ((lane >> 3) & 1)) ^ (lane & 7)) << 4);
      auto dump = [&](float (&U)[36], uint32_t a) {
        pin(U);
        const float r0 = rcp_fast(bf_hi(sv.x)), r1 = rcp_fast(bf_hi(sv.z));
        #pragma unroll
        for (int q = 0; q < 4; q++)
          stsm4t(a + q * 2048, pack_bf16(U[8 * q] * r0, U[8 * q + 1] * r0), pack_bf16(U[8 * q + 2] * r1, U[8 * q + 3] * r1),
                 pack_bf16(U[8 * q + 4] * r0, U[8 * q + 5] * r0), pack_bf16(U[8 * q + 6] * r1, U[8 * q + 7] * r1));
        stsm2t(a + 8192, pack_bf16(U[32] * r0, U[33] * r0), pack_bf16(U[34] * r1, U[35] * r1));
      };
      auto sub = [&](uint32_t* a, int n) {
        #pragma unroll
        for (int i = 0; i < n; i++) asm volatile("sub.rn.bf16x2 %0, %0, %1;" : "+r"(a[i]) : "r"(m2[i & 1]));
      };
      sub(A, 16);
      #pragma unroll
      for (int s = 0; s < 9; s++) {
        const uint32_t sl = (s + 3) & 3;
        if (s > 0 && s < 8) mbar_wait(bars + B_X + 8 * s, 0);
        if (s == 7) ld_x(&A[112], 7);
        if (s > 1 && s < 8) sub(&A[s * 16 - 16], s == 7 ? 32 : 16);
        mbar_wait(bars + B_FULLB + 8 * sl, (s >> 2) & 1);
        if (s < 8) TR(22 + s);
        if (s > 0 && s < 7) ld_x(&A[s * 16], s);
        wg_fence();
        #pragma unroll
        for (int i = 0; i < 2; i++) {
          const int kb = s < 7 ? (s < 2 ? s * 8 : s - 1) : 6 + i, im = s < 7 ? i : 8 - s;
          #pragma unroll
          for (int k = 0; k < 4; k++) {
            const uint32_t bd = lb + sl * (STB / 16) + i * 576 + k * 2;
            if (kb < 8) wgmma_rs72<0>(im ? UI : UR, &A[kb * 16 + k * 4], bd, (s | k) != 0);
            else wgmma_ss72<0, 0>(im ? UI : UR, la8 + k * 2, bd, 1);
            if (s == 0 && i == 0) { sub(&T[4 * k], 4); stsm4(lma ^ (k << 5), T[4 * k], T[4 * k + 1], T[4 * k + 2], T[4 * k + 3]); }
          }
        }
        wg_commit();
        if (s > 0) { wg_wait<1>(); rel(B_EMPTYB + 8 * ((s + 2) & 3)); }
        if (s == 0) { fence_async_smem(); bar_sync(1 + w, 128); }
      }
      dump(UI, da + 9216);
      zero(XG);
      stage(0, false);
      wg_wait<1>();
      rel(B_EMPTYB + 24);
      rg.next();
      TR(2);
      dump(UR, da);
      __syncwarp();
      if (lane == 0) mbar_arrive(bars + B_DUMP);
    }
    TR(3);
    const uint32_t ha = sb + 16384 + w * 8192 + (threadIdx.x & 127) * 16;
    uint32_t pg[16];
    zero(XU);
    #pragma unroll
    for (int i = 0; i < 16; i++) pg[i] = 0;
    auto pack_g = [&]() {
      pin(XG);
      #pragma unroll
      for (int i = 0; i < 16; i++) pg[i] = pack_bf16(XG[2 * i], XG[2 * i + 1]);
    };
    auto make_h = [&](int i0, int i1) {
      pin(XU);
      #pragma unroll
      for (int i = i0; i < i1; i++) pg[i] = bmul2(pg[i], pack_bf16(XU[2 * i], XU[2 * i + 1]));
    };
    #pragma unroll 1
    for (int t = 0; t < 8; t++) {
      const uint32_t hs = ha + (t - 1) * 16384;
      #pragma unroll
      for (int s = 1; s < 10; s++) {
        stage(s % 9, false);
        if (s < 4) make_h(s == 1 ? 0 : 5 * s - 4, 5 * s + 1);
        if (s == 1 && t == 5) mbar_wait(bars + B_SCAN, 0);
        if (s < 5 && t > 0) sts128(hs + (s - 1) * 2048, pg[4 * s - 4], pg[4 * s - 3], pg[4 * s - 2], pg[4 * s - 1]);
        if (s == 6) pack_g();
        wg_wait<1>();
        rel(rg.prev);
        rg.next();
        TRW(6, 3, 19 + s);
      }
      TR(4 + t);
      tt++;
    }
    auto ld_h = [&](int kb) {
      #pragma unroll
      for (int k = 0; k < 4; k++) lds128_tied(&A[kb * 16 + k * 4], ha + (kb % 7) * 16384 + k * 2048);
    };
    make_h(0, 16);
    #pragma unroll
    for (int s = 1; s < 9; s++) {
      stage(s, true);
      if (s == 3) {
        #pragma unroll
        for (int k = 0; k < 4; k++) mov_tied(&A[k * 4], &pg[k * 4], ha);
      }
      if (s > 3) ld_h(s - 3);
      if (s == 5 || s > 6) fence_async_smem();
      wg_wait<1>();
      if (s < 4) rel(rg.prev);
      rg.next();
      if (s == 5 || s > 6) { bar_sync(1 + w, 128); rel(B_EMPTY2 + 8 * (s == 5 ? 0 : s - 6)); }
    }
    Ring2 r2; r2.init();
    const uint32_t l2 = (sd16 + (OFF_R2 >> 4)) | (1u << 16);
    auto g_stage = [&](int s) {
      r2.wait(bars);
      wg_fence();
      #pragma unroll
      for (int k = 0; k < 12; k++) {
        const int kq = s == 2 ? (k + 8) % 12 : k, kk = s * 12 + kq;
        if (kk < 32) wgmma_rs64<1>(XG, &A[((kk + 4) & 31) * 4], l2 + r2.soff() + kq * 128, kk != 0);
        else wgmma_ss64<0, 1>(XG, la8 + (kk - 32) * 2, l2 + r2.soff() + kq * 128, 1);
      }
      wg_commit();
    };
    pack_g();
    g_stage(0);
    ld_h(6);
    fence_async_smem();
    wg_wait<1>();
    r2.next();
    bar_sync(1 + w, 128);
    #pragma unroll
    for (int q = 3; q < 7; q++) rel(B_EMPTY2 + 8 * q);
    g_stage(1);
    ld_h(7);
    make_h(0, 16);
    #pragma unroll
    for (int k = 0; k < 4; k++) stsm4(lma ^ (k << 5), pg[4 * k], pg[4 * k + 1], pg[4 * k + 2], pg[4 * k + 3]);
    fence_async_smem();
    wg_wait<1>(); rel(r2.prev); r2.next();
    bar_sync(1 + w, 128);
    TR(12);
    float S[36];
    zero(S);
    auto s_stage = [&]() {
      r2.wait(bars);
      wg_fence();
      #pragma unroll
      for (int k = 0; k < 4; k++) wgmma_ss72<1, 0>(S, l2 + r2.soff() + w * 512 + k * 128, l2 + r2.soff() + 1024 + k * 2, 1);
      wg_commit();
    };
    const uint32_t ga = sb + 16384 + w * 8192 + warp * 2048;
    #pragma unroll 1
    for (int t = 0; t < 8; t++) {
      g_stage(2); wg_wait<1>(); rel(r2.prev); r2.next();
      s_stage();  wg_wait<1>(); rel(r2.prev); r2.next();
      pack_g();
      g_stage(0);
      mbar_wait(bars + B_STE + 8 * w, (t & 1) ^ 1);
      #pragma unroll
      for (int i = 0; i < 4; i++) stsm4(ga + lane * 16 + i * 512, pg[4 * i], pg[4 * i + 1], pg[4 * i + 2], pg[4 * i + 3]);
      fence_async_smem();
      __syncwarp();
      if (lane == 0) mbar_arrive(bars + B_STF + 8 * w);
      wg_wait<1>(); rel(r2.prev); r2.next();
      g_stage(1); wg_wait<1>(); rel(r2.prev); r2.next();
      if (t == 3) TR(13);
    }
    TR(14);
    g_stage(2); wg_wait<1>(); rel(r2.prev); r2.next();
    s_stage();  wg_wait<1>(); rel(r2.prev); r2.next();
    if (lane == 0) mbar_arrive(bars + B_STF + 8 * w);
    TR(15);
    s_stage(); wg_wait<1>(); rel(r2.prev); r2.next();
    const uint32_t xa = sb + OFF_XT + wid * 2048;
    uint32_t xv[18], tv[18];
    float rr[2];
    {
      mbar_wait(bars + B_XT, 0);
      #pragma unroll
      for (int i = 0; i < 4; i++) ldsm4(&xv[4 * i], (lma ^ (i << 5)) + OFF_XT);
      ldsm2(&xv[16], sb + OFF_XT + 16384 + wid * 256 + (lane & 15) * 16);
      uint32_t dv[9];
      #pragma unroll
      for (int q = 0; q < 9; q++) dv[q] = lds32(sb + OFF_D + q * 16 + c * 4);
      LnC lc;
      #pragma unroll
      for (int h = 0; h < 2; h++) {
        const uint32_t st = lds32(sb + OFF_STAT + (wid * 16 + g + 8 * h) * 4);
        ln_consts(st, lc.m2[h], lc.rh2[h], lc.rl2[h]);
        rr[h] = rcp_fast(bf_hi(st));
        rr[h] *= rr[h];
      }
      s_stage(); wg_wait<1>(); rel(r2.prev); r2.next();
      #pragma unroll
      for (int i = 0; i < 18; i++) tv[i] = bmul2(ln_apply(xv[i], lc.m2[i & 1], lc.rh2[i & 1], lc.rl2[i & 1]), dv[i >> 1]);
    }
    #pragma unroll 1
    for (int i = 11; i < 17; i++) { s_stage(); wg_wait<1>(); if (i < 12) rel(r2.prev); r2.next(); }
    s_stage();
    TR(16);
    {
      uint32_t gv[18];
      mbar_wait(bars + B_GT + 8 * w, 0);
      TR(17);
      #pragma unroll
      for (int i = 0; i < 4; i++) ldsm4(&gv[4 * i], ga + i * 512 + lane * 16);
      ldsm2(&gv[16], sb + w * 8192 + 6144 + warp * 256 + (lane & 15) * 16);
      pin(XG);
      #pragma unroll
      for (int i = 0; i < 18; i++) {
        if (i < 16) gv[i] = pack_bf16((bf_lo(gv[i]) + XG[2 * i]) * rr[i & 1], (bf_hi(gv[i]) + XG[2 * i + 1]) * rr[i & 1]);
        else gv[i] = pack_bf16(bf_lo(gv[i]) * rr[i & 1], bf_hi(gv[i]) * rr[i & 1]);
        const float g0 = bf_lo(gv[i]), g1 = bf_hi(gv[i]);
        gv[i] = pack_bf16(__fdividef(g0, 1.0f + __expf(-g0)), __fdividef(g1, 1.0f + __expf(-g1)));
      }
      wg_wait<0>();
      pin(S);
      TR(18);
      const uint32_t oo = g * 128 + (((c >> 1) ^ g) << 4) + (c & 1) * 8, o8 = sb + w * 8192 + warp * 512;
      #pragma unroll
      for (int i = 0; i < 18; i++) {
        const uint32_t a = i < 16 ? (((i < 8 ? xa : ga) + oo) ^ (((i >> 1) & 3) << 5)) + (i & 1) * 1024 : o8 + lane * 8 + (i & 1) * 256;
        sts64f(a, fmaf(S[2 * i] + bf_lo(tv[i]), bf_lo(gv[i]), bf_lo(xv[i])), fmaf(S[2 * i + 1] + bf_hi(tv[i]), bf_hi(gv[i]), bf_hi(xv[i])));
        if (i == 7 || i == 17) {
          fence_async_smem();
          __syncwarp();
          if (lane == 0) {
            tma2d_st(&P.O, j * 64 + (i == 7 ? 0 : 32), m * 128 + wid * 16, i == 7 ? xa : ga);
            if (i == 17) tma2d_st(&P.O8, 512 + j * 8, m * 128 + wid * 16, o8);
            bulk_commit();
          }
        }
      }
      if (lane == 0) bulk_wait_read();
    }
    TR(19); TRG(31);
    if (threadIdx.x == 0) red_relaxed(sc->epoch + b * 32, 1);
  }
}

typedef CUresult (*EncodeFn)(CUtensorMap*, CUtensorMapDataType, cuuint32_t, void*, const cuuint64_t*, const cuuint64_t*,
                             const cuuint32_t*, const cuuint32_t*, CUtensorMapInterleave, CUtensorMapSwizzle,
                             CUtensorMapL2promotion, CUtensorMapFloatOOBfill);

static void make_map(EncodeFn enc, CUtensorMap* m, const void* base, cuuint64_t cols, cuuint64_t rows, cuuint32_t bc, cuuint32_t br,
                     bool swz = true, bool f32 = false) {
  const cuuint64_t dims[2] = {cols, rows}, strides[1] = {cols * (f32 ? 4 : 2)};
  const cuuint32_t box[2] = {bc, br}, es[2] = {1, 1};
  enc(m, f32 ? CU_TENSOR_MAP_DATA_TYPE_FLOAT32 : CU_TENSOR_MAP_DATA_TYPE_BFLOAT16, 2, (void*)base, dims, strides, box, es,
      CU_TENSOR_MAP_INTERLEAVE_NONE, swz ? CU_TENSOR_MAP_SWIZZLE_128B : CU_TENSOR_MAP_SWIZZLE_NONE,
      CU_TENSOR_MAP_L2_PROMOTION_L2_256B, CU_TENSOR_MAP_FLOAT_OOB_FILL_NONE);
}

}

extern "C" void kernel_launch(void* const* d_in, const int* in_sizes, int n_in, void* d_out, int out_size) {
  using namespace ssmffn;
  void* fn = nullptr;
  cudaDriverEntryPointQueryResult q;
  cudaGetDriverEntryPoint("cuTensorMapEncodeTiled", &fn, cudaEnableDefault, &q);
  EncodeFn enc = (EncodeFn)fn;
  Params P;
  make_map(enc, &P.W[0], d_in[10], 4608, 576, 64, 64);
  make_map(enc, &P.W[1], d_in[11], 4608, 576, 64, 64);
  make_map(enc, &P.Wd, d_in[12], 576, 4608, 64, 96);
  make_map(enc, &P.B[0], d_in[3], 576, 576, 64, 72);
  make_map(enc, &P.B[1], d_in[4], 576, 576, 64, 72);
  make_map(enc, &P.C[0], d_in[5], 576, 576, 64, 64);
  make_map(enc, &P.C[1], d_in[6], 576, 576, 64, 64);
  make_map(enc, &P.C8[0], d_in[5], 576, 576, 64, 8);
  make_map(enc, &P.C8[1], d_in[6], 576, 576, 64, 8);
  make_map(enc, &P.X, d_in[0], 576, 2048, 64, 128);
  make_map(enc, &P.X8, d_in[0], 576, 2048, 8, 128, false);
  make_map(enc, &P.O, d_out, 576, 2048, 32, 16, true, true);
  make_map(enc, &P.O8, d_out, 576, 2048, 8, 16, false, true);
  void* scr = nullptr;
  cudaGetSymbolAddress(&scr, g_scr);
  cudaFuncSetAttribute(fused_kernel, cudaFuncAttributeMaxDynamicSharedMemorySize, SMEM_BYTES);
  fused_kernel<<<NCTA, 384, SMEM_BYTES, cudaStreamPerThread>>>((Scratch*)scr, (const uint8_t*)d_in[0], (const __nv_bfloat16*)d_in[1],
      (const __nv_bfloat16*)d_in[2], (const __nv_bfloat16*)d_in[7], (const uint32_t*)d_in[8], P);
}
```

```cpp
#include <cuda_runtime.h>
#include <cuda.h>
#include <cuda_bf16.h>
#include <stdint.h>

namespace ssmffn {

#define PFM 1
#define PSL 200
#define XH 0
#define STAG 1
#define NI 6
#define SG 16
#define SL 13
#define TH 1
#define N1 0
constexpr int NS = 2 * NI - N1;
#define TVN 384
#define HSH 0
#define SN 8
#define TN 1
#define S2 13
#define PG 2
#define PE 1
#define CS 7
#define X7 4
#define XE 2
#define RUU 5
constexpr int RU = RUU;
#define LB 1
#define SW 0
#define GL 0
#define ER 12
#define E8 0
#define XS 15
#define MH 16
#define NB 1
#define DP 1
#define SI 1
#define DPF 1
#define SO 1
#define PM 2
#define X6 3
#define W0S 5
#define SBS 1
#define NF 1
constexpr int NCTA = 128;
constexpr uint32_t OFF_RING = 131072, ST1 = 16384, NST1 = 6, OFF_RB = 147456, STB = 18432;
constexpr uint32_t OFF_DUMP = 94208, OFF_ZERO = 81920, OFF_COR = OFF_RB + 4 * STB;
constexpr uint32_t OFF_R2 = 32768, ST2 = 25600, NST2 = 7;
constexpr uint32_t OFF_XT = OFF_R2 + NST2 * ST2;
constexpr uint32_t OFF_STAT = OFF_XT + 18432, OFF_D = OFF_STAT + 512, OFF_BAR = OFF_COR + 10368;
constexpr uint32_t B_FULL1 = 0, B_EMPTY1 = 48, B_FULL2 = 96, B_EMPTY2 = 152, B_FULLB = 208, B_EMPTYB = 240, B_X = 272,
                   B_DUMP = 344, B_SCAN = 352, B_STF = 360, B_STE = 376, B_XT = 392, B_GT = 400, B_STAT = 416, B_SB = 424, B_SBD = 432, B_X8 = 440, B_X8D = 448, B_COR = 456;
constexpr uint32_t SPIN_LIMIT = 4000000;

struct Scratch {
  uint4 HS[16 * 18 * 1024];
  uint4 G[16 * 8 * 1152];
  uint4 E[16 * 576];
  uint4 S[16 * 64];
  uint4 TV[NCTA * 1152];
  uint4 SB[576];
  uint32_t cntHS[16 * 32], cntG[32 * 32], epoch[NCTA * 32];
};
__device__ __align__(1024) Scratch g_scr;
#define TR(id)
#define TRG(id)
#define TRS(id)
#define TRINIT
#define TREND
#define TRBYTES 0
constexpr uint32_t SMEM_BYTES = OFF_BAR + 464 + TRBYTES;

struct Params {
  CUtensorMap B[2], W[2], Wd, C[4], X8, O, O8, X;
};

template<int TA, int TB> __device__ __forceinline__ void wgmma_ss64(float (&d)[32], uint32_t alo, uint32_t blo, int sd) {
  asm volatile("{\n.reg .pred p;\n.reg .b64 da, db;\nsetp.ne.b32 p, %35, 0;\nmov.b64 da, {%32, %34};\nmov.b64 db, {%33, %34};\n"
    "wgmma.mma_async.sync.aligned.m64n64k16.f32.bf16.bf16 {%0, %1, %2, %3, %4, %5, %6, %7, %8, %9, %10, %11, %12, %13, %14, %15, %16, %17, %18, %19, %20, %21, %22, %23, %24, %25, %26, %27, %28, %29, %30, %31}, da, db, p, 1, 1, %36, %37;\n}\n"
    : "+f"(d[0]), "+f"(d[1]), "+f"(d[2]), "+f"(d[3]), "+f"(d[4]), "+f"(d[5]), "+f"(d[6]), "+f"(d[7]), "+f"(d[8]), "+f"(d[9]), "+f"(d[10]), "+f"(d[11]), "+f"(d[12]), "+f"(d[13]), "+f"(d[14]), "+f"(d[15]), "+f"(d[16]), "+f"(d[17]), "+f"(d[18]), "+f"(d[19]), "+f"(d[20]), "+f"(d[21]), "+f"(d[22]), "+f"(d[23]), "+f"(d[24]), "+f"(d[25]), "+f"(d[26]), "+f"(d[27]), "+f"(d[28]), "+f"(d[29]), "+f"(d[30]), "+f"(d[31])
    : "r"(alo), "r"(blo), "r"(0x40000040u), "r"(sd), "n"(TA), "n"(TB));
}
template<int TB> __device__ __forceinline__ void wgmma_rs64(float (&d)[32], const uint32_t* a, uint32_t blo, int sd) {
  asm volatile("{\n.reg .pred p;\n.reg .b64 db;\nsetp.ne.b32 p, %38, 0;\nmov.b64 db, {%36, %37};\n"
    "wgmma.mma_async.sync.aligned.m64n64k16.f32.bf16.bf16 {%0, %1, %2, %3, %4, %5, %6, %7, %8, %9, %10, %11, %12, %13, %14, %15, %16, %17, %18, %19, %20, %21, %22, %23, %24, %25, %26, %27, %28, %29, %30, %31}, {%32, %33, %34, %35}, db, p, 1, 1, %39;\n}\n"
    : "+f"(d[0]), "+f"(d[1]), "+f"(d[2]), "+f"(d[3]), "+f"(d[4]), "+f"(d[5]), "+f"(d[6]), "+f"(d[7]), "+f"(d[8]), "+f"(d[9]), "+f"(d[10]), "+f"(d[11]), "+f"(d[12]), "+f"(d[13]), "+f"(d[14]), "+f"(d[15]), "+f"(d[16]), "+f"(d[17]), "+f"(d[18]), "+f"(d[19]), "+f"(d[20]), "+f"(d[21]), "+f"(d[22]), "+f"(d[23]), "+f"(d[24]), "+f"(d[25]), "+f"(d[26]), "+f"(d[27]), "+f"(d[28]), "+f"(d[29]), "+f"(d[30]), "+f"(d[31])
    : "r"(a[0]), "r"(a[1]), "r"(a[2]), "r"(a[3]), "r"(blo), "r"(0x40000040u), "r"(sd), "n"(TB));
}
template<int TA, int TB> __device__ __forceinline__ void wgmma_ss72(float (&d)[36], uint32_t alo, uint32_t blo, int sd) {
  asm volatile("{\n.reg .pred p;\n.reg .b64 da, db;\nsetp.ne.b32 p, %39, 0;\nmov.b64 da, {%36, %38};\nmov.b64 db, {%37, %38};\n"
    "wgmma.mma_async.sync.aligned.m64n72k16.f32.bf16.bf16 {%0, %1, %2, %3, %4, %5, %6, %7, %8, %9, %10, %11, %12, %13, %14, %15, %16, %17, %18, %19, %20, %21, %22, %23, %24, %25, %26, %27, %28, %29, %30, %31, %32, %33, %34, %35}, da, db, p, 1, 1, %40, %41;\n}\n"
    : "+f"(d[0]), "+f"(d[1]), "+f"(d[2]), "+f"(d[3]), "+f"(d[4]), "+f"(d[5]), "+f"(d[6]), "+f"(d[7]), "+f"(d[8]), "+f"(d[9]), "+f"(d[10]), "+f"(d[11]), "+f"(d[12]), "+f"(d[13]), "+f"(d[14]), "+f"(d[15]), "+f"(d[16]), "+f"(d[17]), "+f"(d[18]), "+f"(d[19]), "+f"(d[20]), "+f"(d[21]), "+f"(d[22]), "+f"(d[23]), "+f"(d[24]), "+f"(d[25]), "+f"(d[26]), "+f"(d[27]), "+f"(d[28]), "+f"(d[29]), "+f"(d[30]), "+f"(d[31]), "+f"(d[32]), "+f"(d[33]), "+f"(d[34]), "+f"(d[35])
    : "r"(alo), "r"(blo), "r"(0x40000040u), "r"(sd), "n"(TA), "n"(TB));
}
template<int TB> __device__ __forceinline__ void wgmma_rs72(float (&d)[36], const uint32_t* a, uint32_t blo, int sd) {
  asm volatile("{\n.reg .pred p;\n.reg .b64 db;\nsetp.ne.b32 p, %42, 0;\nmov.b64 db, {%40, %41};\n"
    "wgmma.mma_async.sync.aligned.m64n72k16.f32.bf16.bf16 {%0, %1, %2, %3, %4, %5, %6, %7, %8, %9, %10, %11, %12, %13, %14, %15, %16, %17, %18, %19, %20, %21, %22, %23, %24, %25, %26, %27, %28, %29, %30, %31, %32, %33, %34, %35}, {%36, %37, %38, %39}, db, p, 1, 1, %43;\n}\n"
    : "+f"(d[0]), "+f"(d[1]), "+f"(d[2]), "+f"(d[3]), "+f"(d[4]), "+f"(d[5]), "+f"(d[6]), "+f"(d[7]), "+f"(d[8]), "+f"(d[9]), "+f"(d[10]), "+f"(d[11]), "+f"(d[12]), "+f"(d[13]), "+f"(d[14]), "+f"(d[15]), "+f"(d[16]), "+f"(d[17]), "+f"(d[18]), "+f"(d[19]), "+f"(d[20]), "+f"(d[21]), "+f"(d[22]), "+f"(d[23]), "+f"(d[24]), "+f"(d[25]), "+f"(d[26]), "+f"(d[27]), "+f"(d[28]), "+f"(d[29]), "+f"(d[30]), "+f"(d[31]), "+f"(d[32]), "+f"(d[33]), "+f"(d[34]), "+f"(d[35])
    : "r"(a[0]), "r"(a[1]), "r"(a[2]), "r"(a[3]), "r"(blo), "r"(0x40000040u), "r"(sd), "n"(TB));
}

__device__ __forceinline__ uint32_t smem_u32(const void* p) { return (uint32_t)__cvta_generic_to_shared(p); }
__device__ __forceinline__ void mbar_init(uint32_t bar, uint32_t cnt) { asm volatile("mbarrier.init.shared::cta.b64 [%0], %1;" :: "r"(bar), "r"(cnt)); }
__device__ __forceinline__ void mbar_expect_tx(uint32_t bar, uint32_t bytes) { asm volatile("mbarrier.arrive.expect_tx.shared::cta.b64 _, [%0], %1;" :: "r"(bar), "r"(bytes) : "memory"); }
__device__ __forceinline__ void mbar_arrive(uint32_t bar) { asm volatile("mbarrier.arrive.shared::cta.b64 _, [%0];" :: "r"(bar) : "memory"); }
__device__ __forceinline__ void mbar_arrive_rem(uint32_t rbar) { asm volatile("mbarrier.arrive.shared::cluster.b64 _, [%0];" :: "r"(rbar) : "memory"); }
__device__ __forceinline__ void mbar_wait(uint32_t bar, uint32_t parity) {
  asm volatile("{\n.reg .pred p;\n.reg .u32 c;\n"
    "mbarrier.try_wait.parity.shared::cta.b64 p, [%0], %1;\n"
    "@p bra.uni DONE;\n"
    "mov.u32 c, 0;\n"
    "LOOP:\n"
    "mbarrier.try_wait.parity.shared::cta.b64 p, [%0], %1;\n"
    "@p bra.uni DONE;\n"
    "add.u32 c, c, 1;\n"
    "setp.lt.u32 p, c, %2;\n"
    "@p bra.uni LOOP;\n"
    "trap;\n"
    "DONE:\n}" :: "r"(bar), "r"(parity), "n"(SPIN_LIMIT) : "memory");
}
template<int SLEEP>
__device__ __forceinline__ uint32_t poll_ge(const uint32_t* p, uint32_t target) {
  uint32_t v;
  asm volatile("{\n.reg .pred p;\n.reg .u32 c;\n.reg .s32 d;\n"
    "mov.u32 c, 0;\n"
    "LOOP:\n"
    "ld.acquire.gpu.global.u32 %0, [%1];\n"
    "sub.s32 d, %0, %2;\n"
    "setp.ge.s32 p, d, 0;\n"
    "@p bra DONE;\n"
    "nanosleep.u32 %4;\n"
    "add.u32 c, c, 1;\n"
    "setp.lt.u32 p, c, %3;\n"
    "@p bra LOOP;\n"
    "trap;\n"
    "DONE:\n}" : "=&r"(v) : "l"(p), "r"(target), "n"(SPIN_LIMIT), "n"(SLEEP) : "memory");
  return v;
}
__device__ __forceinline__ uint32_t ld_relaxed(const uint32_t* p) { uint32_t v; asm volatile("ld.relaxed.gpu.global.u32 %0, [%1];" : "=r"(v) : "l"(p) : "memory"); return v; }
__device__ __forceinline__ void st_b128(uint4* p, uint32_t a, uint32_t b, uint32_t c, uint32_t d) {
  asm volatile("{\n.reg .b128 q;\n.reg .b64 l, h;\nmov.b64 l, {%1, %2};\nmov.b64 h, {%3, %4};\nmov.b128 q, {l, h};\nst.relaxed.gpu.global.b128 [%0], q;\n}"
    :: "l"(p), "r"(a), "r"(b), "r"(c), "r"(d) : "memory");
}
__device__ __forceinline__ uint4 ld_b128(const uint4* p) {
  uint4 v;
  asm volatile("{\n.reg .b128 q;\n.reg .b64 l, h;\nld.relaxed.gpu.global.b128 q, [%4];\nmov.b128 {l, h}, q;\nmov.b64 {%0, %1}, l;\nmov.b64 {%2, %3}, h;\n}"
    : "=r"(v.x), "=r"(v.y), "=r"(v.z), "=r"(v.w) : "l"(p) : "memory");
  return v;
}
__device__ __forceinline__ void st_b64(void* p, uint32_t a, uint32_t b) {
  asm volatile("{\n.reg .b64 l;\nmov.b64 l, {%1, %2};\nst.relaxed.gpu.global.b64 [%0], l;\n}" :: "l"(p), "r"(a), "r"(b) : "memory");
}
__device__ __forceinline__ uint4 ld_2xb64(const uint4* p) {
  uint4 v;
  asm volatile("{\n.reg .b64 l, h;\nld.relaxed.gpu.global.v2.b64 {l, h}, [%4];\nmov.b64 {%0, %1}, l;\nmov.b64 {%2, %3}, h;\n}"
    : "=r"(v.x), "=r"(v.y), "=r"(v.z), "=r"(v.w) : "l"(p) : "memory");
  return v;
}
__device__ __forceinline__ uint2 ldg_nc64(const void* p) { uint2 v; asm volatile("ld.global.L1::no_allocate.v2.u32 {%0, %1}, [%2];" : "=r"(v.x), "=r"(v.y) : "l"(p) : "memory"); return v; }
__device__ __forceinline__ bool elect_one() {
  uint32_t p; asm volatile("{\n.reg .pred P;\nelect.sync _|P, 0xffffffff;\nselp.u32 %0, 1, 0, P;\n}" : "=r"(p)); return p;
}
__device__ __forceinline__ void fence_async_global() { asm volatile("fence.proxy.async.global;" ::: "memory"); }
__device__ __forceinline__ void fence_async_smem() { asm volatile("fence.proxy.async.shared::cta;" ::: "memory"); }
#define POLMASK 7
template<int ID> __device__ __forceinline__ uint64_t policy_stream() {
  uint64_t p;
  if ((POLMASK >> ID) & 1) asm volatile("createpolicy.fractional.L2::evict_first.b64 %0, 1.0;" : "=l"(p));
  else asm volatile("createpolicy.fractional.L2::evict_normal.b64 %0, 1.0;" : "=l"(p));
  return p;
}
__device__ __forceinline__ void tma2d(uint32_t dst, const CUtensorMap* m, int c0, int c1, uint32_t bar, uint64_t pol) {
  asm volatile("cp.async.bulk.tensor.2d.shared::cluster.global.mbarrier::complete_tx::bytes.L2::cache_hint [%0], [%1, {%3, %4}], [%2], %5;"
    :: "r"(dst), "l"(m), "r"(bar), "r"(c0), "r"(c1), "l"(pol) : "memory");
}
__device__ __forceinline__ void tma2d_nh(uint32_t dst, const CUtensorMap* m, int c0, int c1, uint32_t bar) {
  asm volatile("cp.async.bulk.tensor.2d.shared::cluster.global.mbarrier::complete_tx::bytes [%0], [%1, {%3, %4}], [%2];"
    :: "r"(dst), "l"(m), "r"(bar), "r"(c0), "r"(c1) : "memory");
}
__device__ __forceinline__ void bulk_ld(uint32_t dst, const void* src, uint32_t bytes, uint32_t bar, uint64_t pol) {
  asm volatile("cp.async.bulk.shared::cluster.global.mbarrier::complete_tx::bytes.L2::cache_hint [%0], [%1], %2, [%3], %4;"
    :: "r"(dst), "l"(src), "r"(bytes), "r"(bar), "l"(pol) : "memory");
}
__device__ __forceinline__ void bulk_ld_nh(uint32_t dst, const void* src, uint32_t bytes, uint32_t bar) {
  asm volatile("cp.async.bulk.shared::cluster.global.mbarrier::complete_tx::bytes [%0], [%1], %2, [%3];"
    :: "r"(dst), "l"(src), "r"(bytes), "r"(bar) : "memory");
}
__device__ __forceinline__ void prefetch_map(const CUtensorMap* m) { asm volatile("prefetch.tensormap [%0];" :: "l"(m) : "memory"); }
__device__ __forceinline__ void wg_fence() { asm volatile("wgmma.fence.sync.aligned;" ::: "memory"); }
__device__ __forceinline__ void wg_commit() { asm volatile("wgmma.commit_group.sync.aligned;" ::: "memory"); }
template<int N> __device__ __forceinline__ void wg_wait() { asm volatile("wgmma.wait_group.sync.aligned %0;" :: "n"(N) : "memory"); }
template<int N> __device__ __forceinline__ void zero(float (&d)[N]) {
  #pragma unroll
  for (int i = 0; i < N; i++) d[i] = 0.f;
}
template<int N> __device__ __forceinline__ void pin(float (&d)[N]) {
  #pragma unroll
  for (int i = 0; i < N; i++) asm volatile("" : "+f"(d[i]) :: "memory");
}
__device__ __forceinline__ void cluster_arrive() { asm volatile("barrier.cluster.arrive.relaxed.aligned;" ::: "memory"); }
__device__ __forceinline__ void cluster_wait() { asm volatile("barrier.cluster.wait.acquire.aligned;" ::: "memory"); }
__device__ __forceinline__ void bar_sync(int id, int n) { asm volatile("bar.sync %0, %1;" :: "r"(id), "r"(n) : "memory"); }
template<int R> __device__ __forceinline__ void reg_alloc() { asm volatile("setmaxnreg.inc.sync.aligned.u32 %0;" :: "n"(R)); }
template<int R> __device__ __forceinline__ void reg_dealloc() { asm volatile("setmaxnreg.dec.sync.aligned.u32 %0;" :: "n"(R)); }

__device__ __forceinline__ uint4 lds128(uint32_t a) {
  uint4 v; asm volatile("ld.shared.v4.u32 {%0, %1, %2, %3}, [%4];" : "=r"(v.x), "=r"(v.y), "=r"(v.z), "=r"(v.w) : "r"(a) : "memory"); return v;
}
__device__ __forceinline__ uint32_t ldg_nc32(const void* p) { uint32_t v; asm volatile("ld.global.nc.u32 %0, [%1];" : "=r"(v) : "l"(p)); return v; }
__device__ __forceinline__ uint32_t ldg_nc16(const void* p) { uint32_t v; asm volatile("ld.global.nc.u16 %0, [%1];" : "=r"(v) : "l"(p)); return v; }
__device__ __forceinline__ void stg128(void* p, uint32_t a, uint32_t b, uint32_t c, uint32_t d) {
  asm volatile("st.global.v4.u32 [%0], {%1, %2, %3, %4};" :: "l"(p), "r"(a), "r"(b), "r"(c), "r"(d) : "memory");
}
__device__ __forceinline__ void sts128(uint32_t a, uint32_t x, uint32_t y, uint32_t z, uint32_t w) {
  asm volatile("st.shared.v4.u32 [%0], {%1, %2, %3, %4};" :: "r"(a), "r"(x), "r"(y), "r"(z), "r"(w) : "memory");
}
__device__ __forceinline__ void sts64f(uint32_t a, float x, float y) { asm volatile("st.shared.v2.f32 [%0], {%1, %2};" :: "r"(a), "f"(x), "f"(y) : "memory"); }
__device__ __forceinline__ uint32_t lds32(uint32_t a) { uint32_t v; asm volatile("ld.shared.u32 %0, [%1];" : "=r"(v) : "r"(a) : "memory"); return v; }
__device__ __forceinline__ uint32_t pack_bf16(float lo, float hi) { uint32_t r; asm("cvt.rn.bf16x2.f32 %0, %1, %2;" : "=r"(r) : "f"(hi), "f"(lo)); return r; }
__device__ __forceinline__ uint32_t bmul2(uint32_t a, uint32_t b) { uint32_t r; asm("mul.rn.bf16x2 %0, %1, %2;" : "=r"(r) : "r"(a), "r"(b)); return r; }
__device__ __forceinline__ uint32_t bsub2(uint32_t a, uint32_t b) { uint32_t r; asm("sub.rn.bf16x2 %0, %1, %2;" : "=r"(r) : "r"(a), "r"(b)); return r; }
__device__ __forceinline__ uint32_t bfma2(uint32_t a, uint32_t b, uint32_t c) { uint32_t r; asm("fma.rn.bf16x2 %0, %1, %2, %3;" : "=r"(r) : "r"(a), "r"(b), "r"(c)); return r; }
__device__ __forceinline__ float bf_lo(uint32_t v) { return __uint_as_float(v << 16); }
__device__ __forceinline__ float bf_hi(uint32_t v) { return __uint_as_float(v & 0xffff0000u); }
__device__ __forceinline__ float bf_round(float v) { return __uint_as_float(pack_bf16(0.f, v)); }
__device__ __forceinline__ float rcp_fast(float v) { float r; asm("rcp.approx.ftz.f32 %0, %1;" : "=f"(r) : "f"(v)); return r; }
__device__ __forceinline__ float silu(float v) {
  float e;
  if (TH) { asm("tanh.approx.f32 %0, %1;" : "=f"(e) : "f"(v)); return bf_round(fmaf(v, e, v)); }
  asm("ex2.approx.ftz.f32 %0, %1;" : "=f"(e) : "f"(v * -1.4426950408889634f));
  return bf_round(v * rcp_fast(1.0f + e));
}
__device__ __forceinline__ void mma_stat(float (&d)[4], uint32_t a, uint32_t b) {
  asm volatile("mma.sync.aligned.m16n8k16.row.col.f32.bf16.bf16.f32 {%0, %1, %2, %3}, {%4, %6, %5, %6}, {%4, %5}, {%0, %1, %2, %3};"
    : "+f"(d[0]), "+f"(d[1]), "+f"(d[2]), "+f"(d[3]) : "r"(a), "r"(b), "r"(0x3F803F80u));
}
__device__ __forceinline__ float2 cmul(float2 a, float2 b) { return make_float2(fmaf(a.x, b.x, -a.y * b.y), fmaf(a.x, b.y, a.y * b.x)); }
__device__ __forceinline__ float2 cfma(float2 a, float2 b, float2 c) { return make_float2(fmaf(a.x, b.x, fmaf(-a.y, b.y, c.x)), fmaf(a.x, b.y, fmaf(a.y, b.x, c.y))); }

__device__ __forceinline__ void ln_consts(uint32_t st, uint32_t& m2, uint32_t& rh2, uint32_t& rl2) {
  m2 = __byte_perm(st, st, 0x1010);
  float r; asm("rcp.approx.ftz.f32 %0, %1;" : "=f"(r) : "f"(bf_hi(st)));
  float rh = bf_round(r);
  rh2 = pack_bf16(rh, rh);
  rl2 = pack_bf16(r - rh, r - rh);
}
__device__ __forceinline__ uint32_t ln_apply(uint32_t x2, uint32_t m2, uint32_t rh2, uint32_t rl2) {
  uint32_t d = bsub2(x2, m2);
  return bfma2(d, rh2, bmul2(d, rl2));
}

__device__ __forceinline__ void tma2d_mc(uint32_t dst, const CUtensorMap* m, int c0, int c1, uint32_t bar, uint64_t pol) {
  asm volatile("cp.async.bulk.tensor.2d.shared::cluster.global.mbarrier::complete_tx::bytes.multicast::cluster.L2::cache_hint [%0], [%1, {%3, %4}], [%2], %5, %6;"
    :: "r"(dst), "l"(m), "r"(bar), "r"(c0), "r"(c1), "h"((uint16_t)3), "l"(pol) : "memory");
}
__device__ __forceinline__ void tma2d_st(const CUtensorMap* m, int c0, int c1, uint32_t src) {
  asm volatile("cp.async.bulk.tensor.2d.global.shared::cta.bulk_group [%0, {%2, %3}], [%1];" :: "l"(m), "r"(src), "r"(c0), "r"(c1) : "memory");
}
__device__ __forceinline__ void bulk_red(void* dst, uint32_t src, uint32_t bytes) {
  asm volatile("cp.reduce.async.bulk.global.shared::cta.bulk_group.add.noftz.bf16 [%0], [%1], %2;" :: "l"(dst), "r"(src), "r"(bytes) : "memory");
}
__device__ __forceinline__ void bulk_st(void* dst, uint32_t src, uint32_t bytes) {
  asm volatile("cp.async.bulk.global.shared::cta.bulk_group [%0], [%1], %2;" :: "l"(dst), "r"(src), "r"(bytes) : "memory");
}
__device__ __forceinline__ void red_relaxed(uint32_t* p, uint32_t v) { asm volatile("red.relaxed.gpu.global.add.u32 [%0], %1;" :: "l"(p), "r"(v) : "memory"); }
__device__ __forceinline__ void bar_arrive(int id, int n) { asm volatile("bar.arrive %0, %1;" :: "r"(id), "r"(n) : "memory"); }
__device__ __forceinline__ void bulk_commit() { asm volatile("cp.async.bulk.commit_group;" ::: "memory"); }
__device__ __forceinline__ void bulk_wait_read() { asm volatile("cp.async.bulk.wait_group.read 0;" ::: "memory"); }
__device__ __forceinline__ void bulk_wait() { asm volatile("cp.async.bulk.wait_group 0;" ::: "memory"); }
__device__ __forceinline__ void ldsm4(uint32_t* r, uint32_t a) {
  asm volatile("ldmatrix.sync.aligned.m8n8.x4.shared.b16 {%0, %1, %2, %3}, [%4];" : "=r"(r[0]), "=r"(r[1]), "=r"(r[2]), "=r"(r[3]) : "r"(a) : "memory");
}
__device__ __forceinline__ void ldsm2(uint32_t* r, uint32_t a) {
  asm volatile("ldmatrix.sync.aligned.m8n8.x2.shared.b16 {%0, %1}, [%2];" : "=r"(r[0]), "=r"(r[1]) : "r"(a) : "memory");
}
__device__ __forceinline__ void stsm4(uint32_t a, uint32_t x, uint32_t y, uint32_t z, uint32_t w) {
  asm volatile("stmatrix.sync.aligned.m8n8.x4.shared.b16 [%0], {%1, %2, %3, %4};" :: "r"(a), "r"(x), "r"(y), "r"(z), "r"(w) : "memory");
}
__device__ __forceinline__ void stsm4t(uint32_t a, uint32_t x, uint32_t y, uint32_t z, uint32_t w) {
  asm volatile("stmatrix.sync.aligned.m8n8.x4.trans.shared.b16 [%0], {%1, %2, %3, %4};" :: "r"(a), "r"(x), "r"(y), "r"(z), "r"(w) : "memory");
}
__device__ __forceinline__ void stsm2t(uint32_t a, uint32_t x, uint32_t y) {
  asm volatile("stmatrix.sync.aligned.m8n8.x2.trans.shared.b16 [%0], {%1, %2};" :: "r"(a), "r"(x), "r"(y) : "memory");
}
__device__ __forceinline__ void mov_tied(uint32_t* r, const uint32_t* v, uint32_t a) {
  asm volatile("{\n.reg .pred p;\nsetp.ne.u32 p, %8, 0;\n@p mov.b32 %0, %4;\n@p mov.b32 %1, %5;\n@p mov.b32 %2, %6;\n@p mov.b32 %3, %7;\n}"
    : "+r"(r[0]), "+r"(r[1]), "+r"(r[2]), "+r"(r[3]) : "r"(v[0]), "r"(v[1]), "r"(v[2]), "r"(v[3]), "r"(a));
}
__device__ __forceinline__ void lds128_tied(uint32_t* r, uint32_t a) {
  asm volatile("{\n.reg .pred p;\nsetp.ne.u32 p, %4, 0;\n@p ld.shared.v4.u32 {%0, %1, %2, %3}, [%4];\n}" : "+r"(r[0]), "+r"(r[1]), "+r"(r[2]), "+r"(r[3]) : "r"(a) : "memory");
}
__device__ __forceinline__ void sts32(uint32_t a, uint32_t v) { asm volatile("st.shared.u32 [%0], %1;" :: "r"(a), "r"(v) : "memory"); }

template<uint32_t FULL, uint32_t EMPTY, uint32_t N, uint32_t SZ>
struct Ring {
  uint32_t st, ph, prev;
  __device__ __forceinline__ void init() { st = 0; ph = 0; prev = 0; }
  __device__ __forceinline__ void wait(uint32_t bars) const { mbar_wait(bars + FULL + 8 * st, ph); }
  __device__ __forceinline__ uint32_t soff() const { return st * (SZ / 16); }
  __device__ __forceinline__ void next() {
    prev = EMPTY + 8 * st;
    if (++st == N) { st = 0; ph ^= 1; }
  }
};
typedef Ring<B_FULL1, B_EMPTY1, NST1, ST1> Ring1;
typedef Ring<B_FULL2, B_EMPTY2, NST2, ST2> Ring2;

#define ROLES(b) \
  const int cl = (b) >> 1, q7 = (cl - 36) * 37 >> 8; \
  const int grp = cl < 4 ? 15 : cl < 36 ? (cl - 4) & 7 : cl - 28 - 7 * q7, mem = cl < 4 ? cl : cl < 36 ? (cl - 4) >> 3 : q7; \
  const int j = mem + (grp >> 3) * 4, m = (grp & 7) * 2 + ((b) & 1);
__device__ __forceinline__ int cta_id() { int v; asm volatile("mov.u32 %0, %%ctaid.x;" : "=r"(v)); return v; }

__device__ __forceinline__ uint32_t thread_id() { uint32_t v; asm volatile("mov.u32 %0, %%tid.x;" : "=r"(v)); return v; }

__global__ void __cluster_dims__(2, 1, 1) __launch_bounds__(384, 1) fused_kernel(Scratch* sc, const uint8_t* px, const uint8_t* pbre, const uint8_t* pbim, const __nv_bfloat16* plre,
    const __nv_bfloat16* plim, const __nv_bfloat16* pldt, const uint32_t* pdskip, float* pout, const __grid_constant__ Params P) {
  extern __shared__ __align__(1024) uint8_t smem_raw[];
  const uint32_t sb = smem_u32(smem_raw);
  const uint32_t bars = sb + OFF_BAR;
  const int b = blockIdx.x;
  const int wid = __shfl_sync(0xffffffffu, threadIdx.x >> 5, 0);
  const int lane = threadIdx.x & 31;
  const int rank = b & 1;
  ROLES(b)
  TRINIT
  TR(0); TRG(30);
  if (wid >= 8) {
    if (wid > 8) cluster_arrive();
    TR(25);
    reg_dealloc<40>();
    TR(26);
    if (elect_one()) {
      if (wid == 8) {
        if (sb & 1023) asm volatile("trap;");
        #pragma unroll
        for (int i = 0; i < 4; i++) { mbar_init(bars + B_FULLB + 8 * i, 1); mbar_init(bars + B_EMPTYB + 8 * i, 4); }
        #pragma unroll
        for (int i = 0; i < 9; i++) mbar_init(bars + B_X + 8 * i, 1);
        mbar_init(bars + B_SB, 1);
      } else if (wid == 9) {
        mbar_init(bars + B_SBD, 3); mbar_init(bars + B_X8, 2); mbar_init(bars + B_X8D, 3); mbar_init(bars + B_COR, 3);
        mbar_init(bars + B_DUMP, 8); mbar_init(bars + B_STAT, 3); mbar_init(bars + B_SCAN, 3); mbar_init(bars + B_XT, 1);
        #pragma unroll
        for (int i = 0; i < 2; i++) { mbar_init(bars + B_STF + 8 * i, 4); mbar_init(bars + B_STE + 8 * i, 1); mbar_init(bars + B_GT + 8 * i, 1); }
      } else if (wid == 10) {
        #pragma unroll
        for (int i = 0; i < NST2; i++) { mbar_init(bars + B_FULL2 + 8 * i, 1); mbar_init(bars + B_EMPTY2 + 8 * i, 4); }
      } else {
        #pragma unroll
        for (int i = 0; i < NST1; i++) { mbar_init(bars + B_FULL1 + 8 * i, 1); mbar_init(bars + B_EMPTY1 + 8 * i, 4); }
      }
      asm volatile("fence.mbarrier_init.release.cluster;" ::: "memory");
    }
    __syncwarp();
    TR(27);
    if (wid == 8) {
      cluster_arrive();
      bar_arrive(3, 384);
      TR(28);
      const uint64_t pn = policy_stream<3>();
      auto ld_x = [&](int kb) {
        mbar_expect_tx(bars + B_X + 8 * kb, 16384);
        if (XH) tma2d(sb + (8 - kb) * 16384, &P.X, kb * 64, m * 128, bars + B_X + 8 * kb, pn);
        else tma2d_nh(sb + (8 - kb) * 16384, &P.X, kb * 64, m * 128, bars + B_X + 8 * kb);
      };
      auto ld_sb = [&]() {
        mbar_expect_tx(bars + B_SB, 10368);
        bulk_ld(sb + OFF_COR, (m < 8 ? pbre : pbim) + (j * 72 + (m & 7) * 9) * 1152, 10368, bars + B_SB, pn);
      };
      if (elect_one()) {
        ld_x(8); prefetch_map(&P.B[rank]);
        ld_x(0);
        ld_x(1);
      }
      __syncwarp();
      TR(3); TRS(31);
      cluster_wait();
      TR(4);
      if (elect_one()) {
        const uint64_t pol = policy_stream<0>();
        const uint32_t wd = sb + OFF_RING + rank * 8192;
        #pragma unroll
        for (int s = 0; s < 14; s++) {
          const uint32_t sl = (s + 3) & 3;
          if (s == PM) {
#pragma unroll 1
            for (int i = 0; i < 12; i++) prefetch_map(&P.B[0] + i);
          }
          if (s == 2) mbar_wait(bars + B_FULLB + 24, 0);
          if (s >= 4 && s < 13) mbar_wait(bars + B_EMPTYB + 8 * sl, (s >> 2) & 1 ^ 1);
          if (s < 9) {
            mbar_expect_tx(bars + B_FULLB + 8 * sl, STB);
            tma2d_mc(sb + OFF_RB + sl * STB + rank * 9216, &P.B[s < 5 ? rank : s < 7], (s < 5 ? (s + 8) % 9 : 6 - 2 * (s & 1) + rank) * 64, j * 72, bars + B_FULLB + 8 * sl, pol);
          }
          if (s == SBS) ld_sb();
          if (s < 4) ld_x(s + 2);
          if (s == X6) ld_x(6);
          if (s == X7) ld_x(7);
          if (s == W0S || s > 8) {
            const int u = s == W0S ? 0 : s - 8;
            mbar_expect_tx(bars + B_FULL1 + 8 * u, ST1);
            tma2d_mc(wd + u * ST1, &P.W[u == 4 ? rank : u == 5], (j * 9 + 6) * 64, (u == 4 ? 8 - 8 * rank : 2 * u % 9 + rank) * 64, bars + B_FULL1 + 8 * u, pol);
          }
          TR(10 + s);
        }
        TR(5);
        uint32_t st = 0, ph = 0;
        auto ld_w = [&](const CUtensorMap* mp, int c0, int c1) {
          mbar_wait(bars + B_EMPTY1 + 8 * st, ph);
          mbar_expect_tx(bars + B_FULL1 + 8 * st, ST1);
          tma2d_mc(wd + st * ST1, mp, c0, c1, bars + B_FULL1 + 8 * st, pol);
          if (++st == NST1) { st = 0; ph ^= 1; }
        };
#pragma unroll 1
        for (int hh = 1; hh < 16; hh++) {
          const int c0 = (j * 9 + (hh < 2 ? 6 : hh < 14 ? (hh >> 1) - 1 : 7)) * 64;
#pragma unroll 1
          for (int c1 = hh < 2 ? 192 + 64 * rank : ((rank ^ hh) & 1) * 64; c1 < 576; c1 += 128) ld_w(&P.W[hh & 1], c0, c1);
        }
        if (DPF) {
          const int q = m >> 1, t = q * 43 >> 7;
          asm volatile("cp.async.bulk.prefetch.tensor.2d.L2.global [%0, {%1, %2}];" :: "l"(&P.Wd), "r"(t ? ((j + t) & 7) * 64 : 512), "r"(j * 576 + rank * 96 + (q - 3 * t) * 192) : "memory");
        }
#pragma unroll 1
        for (int s = 0; s < 9; s++) {
          const int a = (s & 7) == 0 ? 2 * s + rank : s + 1 + 7 * rank;
          ld_w(&P.W[a >= 9], (j * 9 + 8) * 64, (a >= 9 ? a - 9 : a) * 64);
        }
        TR(1);
        st = 0; ph = 0;
        int si = 0;
        const uint8_t* hp = (const uint8_t*)sc->HS + (size_t)m * 294912;
#pragma unroll 1
        for (int i = 0, t = 0, c1 = 0; i < 27; i++) {
          mbar_wait(bars + B_EMPTY2 + 8 * st, ph);
          mbar_expect_tx(bars + B_FULL2 + 8 * st, 24576);
          tma2d_mc(sb + OFF_R2 + st * ST2 + rank * 12288, &P.Wd, t ? ((j + t) & 7) * 64 : 512, j * 576 + rank * 96 + c1, bars + B_FULL2 + 8 * st, pol);
          if (++st == NST2) { st = 0; ph ^= 1; }
          c1 += 192;
          if (c1 == 576) { c1 = 0; t++; }
          if (i == 6) {
            mbar_wait(bars + B_SBD, 0);
            fence_async_global();
            mbar_expect_tx(bars + B_XT, 18432);
            bulk_ld(sb + OFF_XT, sc->TV + b * 1152, 18432, bars + B_XT, pol);
          }
          if (i == 33 - 3 * NI) {
            mbar_wait(bars + B_DUMP, 1);
            mbar_expect_tx(bars + B_XT, 18432);
            tma2d(sb + OFF_XT, &P.X, j * 64, m * 128, bars + B_XT, pol);
            tma2d(sb + OFF_XT + 16384, &P.X8, 512 + j * 8, m * 128, bars + B_XT, pol);
          }
#pragma unroll 1
          for (const int se = i < 25 ? t + NI - 8 + min(t + NI - 8 - (c1 < SO * 192), NI - N1) : i == 25 ? S2 : 18; si < se; si++) {
            const uint32_t fb = bars + B_FULL2 + 8 * st, dst = sb + OFF_R2 + st * ST2;
            const bool c8 = (si & 1) != rank;
            mbar_wait(bars + B_EMPTY2 + 8 * st, ph);
            mbar_expect_tx(fb, ST2);
            if (HSH) { bulk_ld(dst, hp, 8192, fb, pol); bulk_ld(dst + 8192, hp + 147456, 8192, fb, pol); }
            else { bulk_ld_nh(dst, hp, 8192, fb); bulk_ld_nh(dst + 8192, hp + 147456, 8192, fb); }
            tma2d_mc(dst + (c8 ? 24576 : 16384), &P.C[(si >= 9) + 2 * c8], (si >= 9 ? si - 9 : si) * 64, c8 ? 512 + j * 8 : j * 64, fb, pol);
            hp += 8192;
            if (++st == NST2) { st = 0; ph ^= 1; }
          }
        }
        TR(2);
      }
      TREND
    } else {
      bar_sync(3, 384);
      const uint32_t tag = ld_relaxed(sc->epoch + b * 32) + 1;
      const int pl = (wid - 9) * 24 + min(lane, 23), p = j * 72 + pl;
      const uint32_t dsk = ldg_nc32(pdskip + (pl < 32 ? j * 32 + pl : 224 + j * 4 + min(pl, 35)));
      const float lre = bf_lo(ldg_nc16(plre + p)), lim = bf_lo(ldg_nc16(plim + p)), ldt = bf_lo(ldg_nc16(pldt + p));
      const float dt = bf_round(expf(ldt));
      const float er = expf(dt * lre);
      float sn, cs;
      sincosf(dt * lim, &sn, &cs);
      float2 lam = make_float2(er * cs, er * sn);
      const float nr = lam.x - 1.0f, ni = lam.y, den = 2.0f / (lre * lre + lim * lim);
      float2 cf = make_float2((nr * lre + ni * lim) * den, (ni * lre - nr * lim) * den);
      if (PE) asm volatile("" : "+f"(lam.x), "+f"(lam.y), "+f"(cf.x), "+f"(cf.y) :: "memory");
      TR(25);
      auto fetch = [&](const uint4* q, uint4 v) {
        for (uint32_t spin = 0; !__all_sync(0xffffffffu, v.y == tag && v.w == tag); spin++) {
          if (spin > SPIN_LIMIT) asm volatile("trap;");
          if (spin) __nanosleep(PSL);
          v = ld_2xb64(q);
        }
        return v;
      };
      const int h = min((wid - 9) * 32 + lane, 63);
      uint4 sv = make_uint4(0, tag - 1, 0, 0);
      {
        mbar_wait(bars + B_SB, 0);
        TR(8);
        float s0 = 0.f, s1 = 0.f;
        #pragma unroll
        for (int i0 = 0; i0 < 9; i0 += RU) {
          uint4 v[RU];
          #pragma unroll
          for (int i = 0; i < RU; i++) if (i0 + i < 9) v[i] = lds128(sb + OFF_COR + (pl >> 3) * 1152 + (pl & 7) * 16 + (i0 + i) * 128);
          #pragma unroll
          for (int i = 0; i < RU; i++) if (i0 + i < 9) {
            s0 += bf_lo(v[i].x); s1 += bf_hi(v[i].x); s0 += bf_lo(v[i].y); s1 += bf_hi(v[i].y);
            s0 += bf_lo(v[i].z); s1 += bf_hi(v[i].z); s0 += bf_lo(v[i].w); s1 += bf_hi(v[i].w);
          }
          asm volatile("" : "+f"(s0), "+f"(s1) :: "memory");
        }
        s0 += s1;
        float t[7];
        #pragma unroll
        for (int i = 0; i < 7; i++) t[i] = __shfl_xor_sync(0xffffffffu, s0, i + 1);
        s0 = ((s0 + t[0]) + (t[1] + t[2])) + ((t[3] + t[4]) + (t[5] + t[6]));
        if ((pl & 7) == 0) st_b64((uint8_t*)(sc->SB + j * 72 + (m & 7) * 9 + (pl >> 3)) + (m & 8), __float_as_uint(s0), tag);
        TR(10);
      }
      {
        sv = fetch(sc->S + m * 64 + h, sv);
        TR(13);
        uint4 sy = ld_2xb64(sc->SB + p);
        bar_sync(4, 96);
        if (pl < 36) sts32(sb + OFF_D + pl * 4, dsk);
        #pragma unroll
        for (int i = 0; i < 2; i++) {
          const uint32_t st = i ? sv.z : sv.x, m2 = __byte_perm(st, st, 0x1010);
          const uint32_t aa = sb + OFF_COR + ((h & 24) * 2 + (h & 7) + i * 8) * 128 + (((4 + (h >> 5) * 2) ^ (h & 7)) << 4);
          sts32(sb + OFF_STAT + ((h >> 3) * 16 + (h & 7) + i * 8) * 4, st);
          sts128(aa, m2, m2, m2, m2);
          sts128(sb + OFF_COR + pl * 128 + (((2 * i + 1) ^ (pl & 7)) << 4), 0, 0, 0, 0);
        }
        __syncwarp();
        if (lane == 0) mbar_arrive(bars + B_STAT);
        TR(12);
        sy = fetch(sc->SB + p, sy);
        #pragma unroll
        for (int i = 0; i < 2; i++) {
          const float y = -__uint_as_float(i ? sy.z : sy.x), y1 = y - bf_round(y), y2 = y1 - bf_round(y1);
          sts128(sb + OFF_COR + pl * 128 + (((2 * i) ^ (pl & 7)) << 4), pack_bf16(y, y1), pack_bf16(y2, 0.f), 0, 0);
        }
        fence_async_smem();
        __syncwarp();
        if (lane == 0) mbar_arrive(bars + B_COR);
        TR(9);
        mbar_wait(bars + B_STAT, 0);
        mbar_wait(bars + B_X8, 0);
        #pragma unroll 2
        for (int i = threadIdx.x - 288; i < 1024; i += 96) {
          const uint4 v = lds128(sb + i * 16);
          const uint32_t st = lds32(sb + OFF_STAT + (i >> 3) * 4), m2 = __byte_perm(st, st, 0x1010);
          sts128(sb + i * 16, bsub2(v.x, m2), bsub2(v.y, m2), bsub2(v.z, m2), bsub2(v.w, m2));
        }
        fence_async_smem();
        __syncwarp();
        if (lane == 0) mbar_arrive(bars + B_X8D);
        TR(11);
      }
      const uint32_t ua = sb + OFF_DUMP + pl * 128 + ((pl & 7) << 4);
      float2 l128 = lam;
      #pragma unroll
      for (int i = 0; i < 7; i++) l128 = cmul(l128, l128);
      mbar_wait(bars + B_DUMP, 0);
      TR(1);
      {
        const uint32_t stg = sb + OFF_ZERO + (wid - 9) * 3072;
        #pragma unroll
        for (int i = 0; i < 6; i++) sts128(stg + i * 512 + lane * 16, 0, 0, 0, 0);
        fence_async_smem();
        __syncwarp();
        if (lane == 0) {
          uint8_t* z = (uint8_t*)sc->G + (size_t)(m * 8 + j) * 18432 + (wid - 9) * 6144;
          bulk_st(z, stg, 3072); bulk_st(z + 3072, stg, 3072); bulk_commit();
        }
      }
      if (lane < 24) {
        float2 cy = make_float2(0.f, 0.f);
        uint4 nr = lds128(ua), ni = lds128(ua + 9216);
#pragma unroll 2
        for (int ch = 1; ch <= 16; ch++) {
          const uint32_t re[4] = {nr.x, nr.y, nr.z, nr.w}, im[4] = {ni.x, ni.y, ni.z, ni.w};
          const uint32_t u = (ua ^ ((ch & 7) << 4)) + (ch & 8) * 2304;
          nr = lds128(u); ni = lds128(u + 9216);
          #pragma unroll
          for (int q = 0; q < 4; q++) {
            cy = cfma(lam, cy, make_float2(bf_lo(re[q]), bf_lo(im[q])));
            cy = cfma(lam, cy, make_float2(bf_hi(re[q]), bf_hi(im[q])));
          }
        }
        st_b128(sc->E + m * 576 + p, __float_as_uint(cy.x), __float_as_uint(cy.y), tag, tag);
        TR(2);
        cy = make_float2(0.f, 0.f);
#pragma unroll 1
        for (int i0 = 0; i0 < m; i0 += 3) {
          uint4 q[3];
          for (uint32_t spin = 0;; spin++) {
            #pragma unroll
            for (int i = 0; i < 3; i++) q[i] = ld_b128(sc->E + (i0 + i) * 576 + p);
            if (__all_sync(0xffffffu, q[0].z == tag && q[1].z == tag && q[2].z == tag)) break;
            if (spin > SPIN_LIMIT) asm volatile("trap;");
          }
          #pragma unroll
          for (int i = 0; i < 3; i++)
            if (i0 + i < m) cy = cfma(l128, cy, make_float2(__uint_as_float(q[i].x), __uint_as_float(q[i].y)));
        }
        TR(3);
        nr = lds128(ua); ni = lds128(ua + 9216);
        cy = cmul(cf, cy);
        cy.y = -cy.y;
        auto step = [&](float ur, float ui) {
          const float tx = __fmaf_rn(lam.y, cy.y, __fmul_rn(lam.x, cy.x)), ty = __fmaf_rn(-lam.y, cy.x, __fmul_rn(lam.x, cy.y));
          cy.x = __fmaf_rn(-cf.y, ui, __fmaf_rn(cf.x, ur, tx));
          cy.y = __fmaf_rn(-cf.y, ur, __fmaf_rn(-cf.x, ui, ty));
        };
#pragma unroll 2
        for (int ch = 1; ch <= 16; ch++) {
          uint32_t re[4] = {nr.x, nr.y, nr.z, nr.w}, im[4] = {ni.x, ni.y, ni.z, ni.w};
          const uint32_t u = (ua ^ ((ch & 7) << 4)) + (ch & 8) * 2304;
          nr = lds128(u); ni = lds128(u + 9216);
          #pragma unroll
          for (int q = 0; q < 4; q++) {
            step(bf_lo(re[q]), bf_lo(im[q]));
            const float2 a = cy;
            step(bf_hi(re[q]), bf_hi(im[q]));
            re[q] = pack_bf16(a.x, cy.x);
            im[q] = pack_bf16(a.y, cy.y);
          }
          const uint32_t o = (ua ^ (((ch - 1) & 7) << 4)) + ((ch - 1) & 8) * 2304;
          sts128(o, re[0], re[1], re[2], re[3]);
          sts128(o + 9216, im[0], im[1], im[2], im[3]);
        }
      }
      fence_async_smem();
      __syncwarp();
      if (lane == 0) {
        uint8_t* hs = (uint8_t*)sc->HS + (size_t)m * 294912 + p * 128;
        #pragma unroll
        for (int i = 0; i < 4; i++) bulk_st(hs + i * 73728, ua + i * 9216, 3072);
        bulk_commit();
        bulk_wait_read();
        mbar_arrive(bars + B_SCAN);
        bulk_wait();
        red_relaxed(sc->cntHS + m * 32, 1);
      }
      TR(4);
      __syncwarp();
      {
      const int b = cta_id();
      ROLES(b)
#pragma unroll 1
      for (int u = threadIdx.x - 288; u < TVN; u += 96) {
        const int r = u & 127;
        uint32_t m2, rh2, rl2;
        ln_consts(lds32(sb + OFF_STAT + r * 4), m2, rh2, rl2);
#pragma unroll 1
        for (int cc = (u >> 7) * 3; cc < (u >> 7) * 3 + 3; cc++) {
          const uint4 v = __ldg((const uint4*)(px + (size_t)(m * 128 + r) * 1152 + (cc < 8 ? j * 128 + cc * 16 : 1024 + j * 16)));
          const uint4 d = lds128(sb + OFF_D + cc * 16);
          stg128(sc->TV + b * 1152 + cc * 128 + r, bmul2(ln_apply(v.x, m2, rh2, rl2), d.x), bmul2(ln_apply(v.y, m2, rh2, rl2), d.y),
                 bmul2(ln_apply(v.z, m2, rh2, rl2), d.z), bmul2(ln_apply(v.w, m2, rh2, rl2), d.w));
        }
      }
      const uint32_t tag = ld_relaxed(sc->epoch + b * 32) + 1;
      if (lane == 0) poll_ge<200>(sc->cntHS + m * 32, tag * 24);
      fence_async_global();
      __syncwarp();
      if (lane == 0) mbar_arrive(bars + B_SBD);
      TR(6);
      if (wid < 11) {
        const int w = wid - 9;
        if (lane == 0) {
          uint8_t* gp = (uint8_t*)sc->G + (size_t)(m * 2 + w) * 73728;
          uint32_t* cnt = sc->cntG + (m * 2 + w) * 32;
#pragma unroll 1
          for (int t = 0; t < 8; t++) {
            const int a = t ? (j + t) & 7 : 8;
            mbar_wait(bars + B_STF + 8 * w, t & 1);
            fence_async_smem();
            bulk_red(gp + a * 8192, sb + 16384 + w * 8192, 8192);
            bulk_commit();
            bulk_wait();
            red_relaxed(cnt + a, 1);
            mbar_arrive(bars + B_STE + 8 * w);
            if (t == 4) poll_ge<100>(cnt + 8, tag * 8);
          }
          TR(5);
          poll_ge<20>(cnt + j, tag * 7);
          mbar_arrive(bars + B_GT + 8 * w);
          TR(7);
        }
      }
      }
      TREND
    }
  } else {
#define TQ
    if (PFM && threadIdx.x == 224) {
      prefetch_map(&P.X); prefetch_map(&P.B[rank]);
    }
    cluster_arrive();
    const int w = wid >> 2, warp = wid & 3, g = lane >> 2, c = lane & 3;
    const uint32_t lma = sb + w * 8192 + (warp * 16 + (lane & 15)) * 128 + (((lane >> 4) ^ (lane & 7)) << 4);
    uint32_t A[128];
    auto ld_x = [&](uint32_t* a, int kb) {
      #pragma unroll
      for (int k = 0; k < 4; k++) ldsm4(a + k * 4, (lma ^ (k << 5)) + (8 - kb) * 16384);
    };
    {
      uint2 xr[9];
      const uint8_t* xp = px + (size_t)(m * 128 + j * 16 + wid + (lane >> 4) * 8) * 1152 + (lane & 15) * 8;
      const uint32_t tag = ld_relaxed(sc->epoch + b * 32) + 1;
      if (PFM > 2) bar_sync(3, 384);
      #pragma unroll
      for (int i = 0; i < 9; i++) xr[i] = ldg_nc64(xp + ((i + 8) % 9) * 128);
      if (PFM <= 2) bar_sync(3, 384);
      reg_alloc<232>();
      float d[3][4];
      #pragma unroll
      for (int i = 0; i < 12; i++) d[i >> 2][i & 3] = 0.f;
      #pragma unroll
      for (int i = 0; i < 9; i++) mma_stat(d[i % 3], xr[i].x, xr[i].y);
      float sm = (d[0][2] + d[0][3]) + (d[1][2] + d[1][3]) + (d[2][2] + d[2][3]);
      float sq = (g & 1) ? d[0][1] + d[1][1] + d[2][1] : d[0][0] + d[1][0] + d[2][0];
      if (c != (g >> 1)) sq = 0.f;
      sm += __shfl_xor_sync(0xffffffffu, sm, 1);
      sq += __shfl_xor_sync(0xffffffffu, sq, 1);
      sq += __shfl_xor_sync(0xffffffffu, sq, 4);
      sq += __shfl_xor_sync(0xffffffffu, sq, 8);
      const float mean = sm * (1.0f / 576.0f);
      const float var = fmaxf(fmaf(-mean, mean, sq * (1.0f / 576.0f)), 0.f);
      float sd; asm("sqrt.approx.ftz.f32 %0, %1;" : "=f"(sd) : "f"(bf_round(bf_round(var) + 1e-5f)));
      if (lane == 0 || lane == 18) st_b64((uint8_t*)(sc->S + (m * 8 + j) * 8 + wid) + (lane >> 4) * 8, pack_bf16(mean, sd), tag);
      TR(20);
    }
    const bool elected = (threadIdx.x & 126) == 0;
    uint32_t rbar;
    asm("mapa.shared::cluster.u32 %0, %1, %2;" : "=r"(rbar) : "r"(bars), "r"(lane & 1));
    auto rel = [&](uint32_t off) { if (elected) mbar_arrive_rem(rbar + off); };
    const uint32_t sd16 = (sb & 0x3FFFF) >> 4;
    const uint32_t la8 = (sd16 + w * 512) | (1u << 16);
    float XG[32], XU[32];
    auto ld_stat = [&](uint32_t (&sv)[2]) {
      sv[0] = lds32(sb + OFF_STAT + (wid * 16 + g) * 4); sv[1] = lds32(sb + OFF_STAT + (wid * 16 + g + 8) * 4);
    };
    auto sub = [&](uint32_t* a, int n, const uint32_t (&sv)[2]) {
      const uint32_t m2[2] = {__byte_perm(sv[0], sv[0], 0x1010), __byte_perm(sv[1], sv[1], 0x1010)};
      #pragma unroll
      for (int i = 0; i < n; i++) asm volatile("sub.rn.bf16x2 %0, %0, %1;" : "+r"(a[i]) : "r"(m2[i & 1]));
    };
    Ring1 rg; rg.init();
    int tt = 0;
    auto stage = [&](int s, bool last) {
      const uint32_t lb = (sd16 + (OFF_RING >> 4)) | (1u << 16);
      TQ
      rg.wait(bars);
      wg_fence();
      #pragma unroll
      for (int i = 0; i < 2; i++) {
        const int a = (!last || s == 8) ? 2 * s + i : s + 1 + 7 * i, kb = a % 9;
        #pragma unroll
        for (int k = 0; k < 4; k++) {
          const uint32_t bd = lb + rg.soff() + i * 512 + k * 128;
          if (kb < 8) wgmma_rs64<1>(a < 9 ? XG : XU, &A[kb * 16 + k * 4], bd, (kb | k) != 0);
          else wgmma_ss64<0, 1>(a < 9 ? XG : XU, la8 + k * 2, bd, 1);
        }
      }
      wg_commit();
    };
    {
      float UR[36], UI[36];
      zero(UR); zero(UI);
      const uint32_t lb = (sd16 + (OFF_RB >> 4)) | (1u << 16);
      const uint32_t da = sb + OFF_DUMP + w * 18432 + ((lane >> 4) * 8 + (lane & 7)) * 128 + (((warp * 2 + ((lane >> 3) & 1)) ^ (lane & 7)) << 4);
      uint32_t sv[2];
      auto dump = [&](float (&U)[36], uint32_t a) {
        pin(U);
        const float r0 = rcp_fast(bf_hi(sv[0])), r1 = rcp_fast(bf_hi(sv[1]));
        #pragma unroll
        for (int q = 0; q < 4; q++)
          stsm4t(a + q * 2048, pack_bf16(U[8 * q] * r0, U[8 * q + 1] * r0), pack_bf16(U[8 * q + 2] * r1, U[8 * q + 3] * r1),
                 pack_bf16(U[8 * q + 4] * r0, U[8 * q + 5] * r0), pack_bf16(U[8 * q + 6] * r1, U[8 * q + 7] * r1));
        stsm2t(a + 8192, pack_bf16(U[32] * r0, U[33] * r0), pack_bf16(U[34] * r1, U[35] * r1));
      };
      mbar_wait(bars + B_X + 64, 0);
      TR(1);
      #pragma unroll
      for (int k = 0; k < XE; k++) { mbar_wait(bars + B_X + 8 * k, 0); ld_x(&A[k * 16], k); }
      if (STAG && w == 1) bar_sync(5, 256);
      #pragma unroll
      for (int s = 0; s < 9; s++) {
        const uint32_t sl = (s + 3) & 3;
        mbar_wait(bars + B_FULLB + 8 * sl, (s >> 2) & 1);
        if (s < 8) TR(22 + s);
        wg_fence();
        #pragma unroll
        for (int i = 0; i < 2; i++) {
          const int kb = s < 5 ? (s + 8) % 9 : 6 - 2 * (s & 1) + i, im = s < 5 ? i : s < 7;
          if (s == CS) wgmma_ss72<0, 0>(i ? UI : UR, lb + 4 * (STB / 16) + 4 + w * 2, lb + 4 * (STB / 16) + i * 2, 1);
          #pragma unroll
          for (int k = 0; k < 4; k++) {
            const uint32_t bd = lb + sl * (STB / 16) + i * 576 + k * 2;
            if (kb < 8) wgmma_rs72<0>(im ? UI : UR, &A[kb * 16 + k * 4], bd, 1);
            else wgmma_ss72<0, 0>(im ? UI : UR, la8 + k * 2, bd, k != 0);
          }
        }
        wg_commit();
        if (STAG && s == 0 && w == 0) bar_arrive(5, 256);
        if (LB && s < 6) { mbar_wait(bars + B_X + 8 * s + 16, 0); ld_x(&A[s * 16 + 32], s + 2); }
        if (s == 6) {
          mbar_wait(bars + B_STAT, 0);
          TR(21);
          ld_stat(sv);
        }
        if (s == 6 || s == 7) sub(&A[32 * s - 192], 32, sv);
        if (s == 8 && CS < 7) dump(UI, da + 9216);
        if (s > 0) { wg_wait<1>(); rel(B_EMPTYB + 8 * ((s + 2) & 3)); }
        if (s == 8 && CS == 7) dump(UI, da + 9216);
        if (s == 1 && (threadIdx.x & 127) == 0) mbar_arrive(bars + B_X8);
        if (!LB && s < 6) { mbar_wait(bars + B_X + 8 * s + 16, 0); ld_x(&A[s * 16 + 32], s + 2); }
        if (s == CS - 1) mbar_wait(bars + B_COR, 0);
      }
      zero(XG);
      #pragma unroll
      for (int s = 0; s < 4; s++) {
        stage(s, false);
        if (SW && (s == 0 || s == 2)) sub(&A[64 + 16 * s], 32, sv);
        if (s == 1) {
          dump(UR, da);
          __syncwarp();
          if (lane == 0) mbar_arrive(bars + B_DUMP);
          TR(3);
        }
        wg_wait<1>();
        rel(s == 0 ? B_EMPTYB + 24 : rg.prev);
        rg.next();
        if (s == 0) TR(2);
        if (!SW && s < 3) sub(&A[s ? 80 + 16 * s : 64], s ? 16 : 32, sv);
        if (s == 3) mbar_wait(bars + B_X8D, 0);
      }
    }
    const uint32_t ha = sb + 16384 + w * 8192 + (threadIdx.x & 127) * 16;
    uint32_t pg[16];
    zero(XU);
    #pragma unroll
    for (int i = 0; i < 16; i++) pg[i] = 0;
    auto pack = [&](float (&D)[32]) {
      pin(D);
      #pragma unroll
      for (int i = 0; i < 16; i++) pg[i] = pack_bf16(D[2 * i], D[2 * i + 1]);
    };
    auto make_h = [&](int i0, int i1) {
      pin(XU);
      #pragma unroll
      for (int i = i0; i < i1; i++) pg[i] = bmul2(pg[i], pack_bf16(XU[2 * i], XU[2 * i + 1]));
    };
    #pragma unroll 1
    for (int t = 0;; t++) {
      const uint32_t hs = ha + t * 16384;
      #pragma unroll
      for (int s = 4; s < 10; s++) {
        stage(s % 9, false);
        if (s == 4 && t > 0) sts128(hs - 16384 + 6144, pg[12], pg[13], pg[14], pg[15]);
        if (s == 6) pack(XG);
        wg_wait<1>();
        rel(rg.prev);
        rg.next();
      }
      TR(4 + t);
      if (t == 7) break;
      #pragma unroll
      for (int s = 1; s < 4; s++) {
        stage(s, false);
        make_h(s == 1 ? 0 : 5 * s - 4, 5 * s + 1);
        if (s == 1 && t == 4) mbar_wait(bars + B_SCAN, 0);
        sts128(hs + (s - 1) * 2048, pg[4 * s - 4], pg[4 * s - 3], pg[4 * s - 2], pg[4 * s - 1]);
        wg_wait<1>();
        rel(rg.prev);
        rg.next();
      }
    }
    auto ld_h = [&](int kb) {
      #pragma unroll
      for (int k = 0; k < 4; k++) lds128_tied(&A[kb * 16 + k * 4], ha + (kb % 7) * 16384 + k * 2048);
    };
    make_h(0, 16);
    #pragma unroll
    for (int s = 1; s < 9; s++) {
      stage(s, true);
      if (s == 3) {
        #pragma unroll
        for (int k = 0; k < 4; k++) mov_tied(&A[k * 4], &pg[k * 4], ha);
      }
      if (s > 3) ld_h(s - 3);
      if (!NF && (s == 5 || s > 6)) fence_async_smem();
      wg_wait<1>();
      if (s < 4) rel(rg.prev);
      rg.next();
      if (s == 5 || s > 6) { bar_sync(1 + w, 128); rel(B_EMPTY2 + 8 * (s == 5 ? 0 : s - 6)); }
    }
    Ring2 r2; r2.init();
    const uint32_t l2 = (sd16 + (OFF_R2 >> 4)) | (1u << 16);
    const uint32_t ga = sb + 16384 + w * 8192 + warp * 2048;
    auto put_g = [&]() {
      #pragma unroll
      for (int i = 0; i < 4; i++) sts128(ga + lane * 16 + i * 512, pg[4 * i], pg[4 * i + 1], pg[4 * i + 2], pg[4 * i + 3]);
      __syncwarp();
      if (lane == 0) mbar_arrive(bars + B_STF + 8 * w);
    };
    auto g_stage = [&](float (&D)[32], int s, bool put = false, int early = 12) {
      TQ
      r2.wait(bars);
      wg_fence();
      #pragma unroll
      for (int k = 0; k < 12; k++) {
        if (put && k == PG) put_g();
        if (k == early) { wg_commit(); wg_wait<1>(); rel(r2.prev); wg_fence(); }
        const int kq = s == 2 ? (k + 8) % 12 : k, kk = s * 12 + kq;
        if (kk < 32) wgmma_rs64<1>(D, &A[((kk + 4) & 31) * 4], l2 + r2.soff() + kq * 128, kk != 0);
        else wgmma_ss64<0, 1>(D, la8 + (kk - 32) * 2, l2 + r2.soff() + kq * 128, 1);
      }
      wg_commit();
    };
    pack(XG);
    g_stage(XG, 0);
    ld_h(6);
    if (!NF) fence_async_smem();
    wg_wait<1>();
    r2.next();
    bar_sync(1 + w, 128);
    #pragma unroll
    for (int q = 3; q < 7; q++) rel(B_EMPTY2 + 8 * q);
    if (MH) make_h(0, MH);
    g_stage(XG, 1);
    ld_h(7);
    make_h(MH, 16);
    #pragma unroll
    for (int k = 0; k < 4; k++) stsm4(lma ^ (k << 5), pg[4 * k], pg[4 * k + 1], pg[4 * k + 2], pg[4 * k + 3]);
    fence_async_smem();
    wg_wait<1>(); rel(r2.prev); r2.next();
    if (NB) __syncwarp(); else bar_sync(1 + w, 128);
    #pragma unroll
    for (int i = 0; i < 8 - NI; i++) {
      g_stage(i & 1 ? XU : XG, 2); wg_wait<1>(); rel(r2.prev); r2.next();
      g_stage(i & 1 ? XG : XU, 0);
      if (DP && i) mbar_wait(bars + B_STE + 8 * w, i & 1 ^ 1);
      wg_wait<1>(); rel(r2.prev); r2.next();
      if (DP) pack(i & 1 ? XU : XG);
      if (DP == 2) put_g();
      g_stage(i & 1 ? XG : XU, 1, DP == 1);
      if (!DP) {
        pack(i & 1 ? XU : XG);
        if (i) mbar_wait(bars + B_STE + 8 * w, i & 1 ^ 1);
        put_g();
      }
      if (i < 7 - NI || !SI) { wg_wait<1>(); rel(r2.prev); r2.next(); }
    }
    float S[36];
    {
      uint32_t tv[18];
      mbar_wait(bars + B_XT, 0);
      #pragma unroll
      for (int i = 0; i < 4; i++) ldsm4(&tv[4 * i], sb + OFF_XT + (2 * i + (lane >> 4)) * 2048 + wid * 256 + (lane & 15) * 16);
      ldsm2(&tv[16], sb + OFF_XT + 16384 + wid * 256 + (lane & 15) * 16);
      #pragma unroll
      for (int i = 0; i < 18; i++) { S[2 * i] = bf_lo(tv[i]); S[2 * i + 1] = bf_hi(tv[i]); }
      pin(S);
      if (lane == 0) mbar_arrive(bars + B_DUMP);
      if (SI) { wg_wait<1>(); rel(r2.prev); r2.next(); }
    }
    auto s_stage = [&]() {
      TQ
      r2.wait(bars);
      wg_fence();
      #pragma unroll
      for (int k = 0; k < 4; k++) wgmma_ss72<1, 0>(S, l2 + r2.soff() + w * 512 + k * 128, l2 + r2.soff() + 1024 + k * 2, 1);
      wg_commit();
    };
    auto g_tile = [&](int t, bool two) {
      g_stage(XG, 2); wg_wait<1>(); rel(r2.prev); r2.next();
      s_stage();
      mbar_wait(bars + B_STE + 8 * w, (t & 1) ^ 1);
      wg_wait<1>(); rel(r2.prev); r2.next();
      if (two && SO == 0) s_stage();
      pack(XG);
      if (two && SO == 0) { wg_wait<1>(); rel(r2.prev); r2.next(); }
      g_stage(XG, 0, true); wg_wait<1>(); rel(r2.prev); r2.next();
      if (two && SO == 1) { s_stage(); wg_wait<1>(); rel(r2.prev); r2.next(); }
      g_stage(XG, 1); wg_wait<1>(); rel(r2.prev); r2.next();
    };
    #pragma unroll 1
    for (int t = 0; t < NI - N1; t++) g_tile(t, true);
    #pragma unroll 1
    for (int t = NI - N1; t < NI; t++) g_tile(t, false);
    TR(14);
    {
    const int b = cta_id();
    const uint32_t tid = thread_id();
    ROLES(b)
    r2.st = (26 + NS) % 7; r2.ph = (26 + NS) / 7 & 1; r2.prev = B_EMPTY2 + (25 + NS) % 7 * 8;
    const uint32_t xa = sb + OFF_XT + wid * 2048;
    const uint8_t* gp = (const uint8_t*)sc->G + (size_t)m * 147456 + (tid >> 7) * 73728 + (tid & 96) * 64 + (tid & 31) * 16;
    uint32_t xv[18], gv[18], st[2];
    float rr[2], sg[36], u[36];
    auto gate = [&](int i) {
      const float v = i & 1 ? bf_hi(gv[i >> 1]) : bf_lo(gv[i >> 1]);
      sg[i] = silu(bf_round(i >= 32 ? v * rr[(i >> 1) & 1] : XS ? fmaf(v, rr[(i >> 1) & 1], XG[i & 31]) : (v + XG[i & 31]) * rr[(i >> 1) & 1]));
    };
    #pragma unroll
    for (int s = NS; s < 18; s++) {
      if (s == S2) { g_stage(XG, 2, false, ER); if (S2 < 13 && ER == 12) { wg_wait<1>(); rel(r2.prev); } r2.next(); TR(15); }
      if (GL) s_stage();
      if (s == SL) {
        mbar_wait(bars + B_GT + 8 * w, 0);
        TR(17);
        #pragma unroll
        for (int i = 0; i < 4; i++) {
          const uint4 v = ld_2xb64((const uint4*)(gp + j * 8192 + i * 512));
          gv[4 * i] = v.x; gv[4 * i + 1] = v.y; gv[4 * i + 2] = v.z; gv[4 * i + 3] = v.w;
        }
        if (!E8) asm volatile("ld.relaxed.gpu.global.v2.u32 {%0, %1}, [%2];" : "=r"(gv[16]), "=r"(gv[17]) : "l"(gp + 65536 + (j >> 1) * 512 + (j & 1) * 8) : "memory");
      }
      if (!GL) s_stage();
      if (s == NS) {
        mbar_wait(bars + B_XT, 1);
        #pragma unroll
        for (int i = 0; i < 4; i++) ldsm4(&xv[4 * i], (lma ^ (i << 5)) + OFF_XT);
        ldsm2(&xv[16], sb + OFF_XT + 16384 + wid * 256 + (lane & 15) * 16);
        ld_stat(st);
        if (E8) asm volatile("ld.relaxed.gpu.global.v2.u32 {%0, %1}, [%2];" : "=r"(gv[16]), "=r"(gv[17]) : "l"(gp + 65536 + (j >> 1) * 512 + (j & 1) * 8) : "memory");
      }
      if (s == NS + 1) {
        #pragma unroll
        for (int h = 0; h < 2; h++) { rr[h] = rcp_fast(bf_hi(st[h])); rr[h] *= (TH ? 0.5f : 1.0f) * rr[h]; }
      }
      if (s == (XS ? XS : SG)) {
        wg_wait<(XS ? XS : SG) - S2 + 1>(); pin(XG);
        if (XS) {
          #pragma unroll
          for (int i = 0; i < 32; i++) XG[i] *= rr[(i >> 1) & 1];
          pin(XG);
        }
      }
      #pragma unroll
      for (int i = 0; i < 36; i++) {
        if (i / 12 + NS + 1 == s) {
          u[i] = i & 1 ? bf_hi(xv[i >> 1]) : bf_lo(xv[i >> 1]);
          asm volatile("" : "+f"(u[i]) :: "memory");
        }
        if (i < SN && i * (18 - SG) / SN + SG == s || E8 && i >= 32 && s == E8) {
          gate(i);
          asm volatile("" : "+f"(sg[i]) :: "memory");
        }
      }
      if (s < (S2 > 12 ? 13 : 12)) { wg_wait<1>(); rel(r2.prev); }
      r2.next();
    }
    TR(13);
    wg_wait<0>();
    pin(S);
    TR(18);
    {
      const uint32_t oo = g * 128 + (((c >> 1) ^ g) << 4) + (c & 1) * 8;
      float* op = pout + (m * 128 + (tid >> 5) * 16 + (tid >> 2 & 7)) * 576 + (tid & 3) * 2;
      #pragma unroll
      for (int i = 0; i < 18; i++) {
        if (2 * i >= SN && !(E8 && i >= 16)) { gate(2 * i); gate(2 * i + 1); }
        const float o0 = fmaf(S[2 * i], sg[2 * i], u[2 * i]), o1 = fmaf(S[2 * i + 1], sg[2 * i + 1], u[2 * i + 1]);
        if (i < TN * 8) sts64f((((i < 8 ? xa : ga) + oo) ^ (((i >> 1) & 3) << 5)) + (i & 1) * 1024, o0, o1);
        else asm volatile("st.global.v2.f32 [%0], {%1, %2};" :: "l"(op + (i & 1) * 4608 + (i < 16 ? j * 64 + (i >> 1) * 8 : 512 + j * 8)), "f"(o0), "f"(o1) : "memory");
        if (i == TN * 8 - 1) {
          fence_async_smem();
          __syncwarp();
          if (lane == 0) {
            tma2d_st(&P.O, j * 64, m * 128 + wid * 16, xa);
            if (TN == 2) tma2d_st(&P.O, j * 64 + 32, m * 128 + wid * 16, ga);
            bulk_commit();
          }
        }
      }
      if (TN && lane == 0) bulk_wait_read();
    }
    TR(19); TRG(31);
    TREND
    if (threadIdx.x == 0) red_relaxed(sc->epoch + b * 32, 1);
    }
  }
}

typedef CUresult (*EncodeFn)(CUtensorMap*, CUtensorMapDataType, cuuint32_t, void*, const cuuint64_t*, const cuuint64_t*,
                             const cuuint32_t*, const cuuint32_t*, CUtensorMapInterleave, CUtensorMapSwizzle,
                             CUtensorMapL2promotion, CUtensorMapFloatOOBfill);

static void make_map(EncodeFn enc, CUtensorMap* m, const void* base, cuuint64_t cols, cuuint64_t rows, cuuint32_t bc, cuuint32_t br,
                     bool swz = true, bool f32 = false) {
  const cuuint64_t dims[2] = {cols, rows}, strides[1] = {cols * (f32 ? 4 : 2)};
  const cuuint32_t box[2] = {bc, br}, es[2] = {1, 1};
  enc(m, f32 ? CU_TENSOR_MAP_DATA_TYPE_FLOAT32 : CU_TENSOR_MAP_DATA_TYPE_BFLOAT16, 2, (void*)base, dims, strides, box, es,
      CU_TENSOR_MAP_INTERLEAVE_NONE, swz ? CU_TENSOR_MAP_SWIZZLE_128B : CU_TENSOR_MAP_SWIZZLE_NONE,
      CU_TENSOR_MAP_L2_PROMOTION_L2_256B, CU_TENSOR_MAP_FLOAT_OOB_FILL_NONE);
}

}

extern "C" void kernel_launch(void* const* d_in, const int* in_sizes, int n_in, void* d_out, int out_size) {
  using namespace ssmffn;
  void* fn = nullptr;
  cudaDriverEntryPointQueryResult q;
  cudaGetDriverEntryPoint("cuTensorMapEncodeTiled", &fn, cudaEnableDefault, &q);
  EncodeFn enc = (EncodeFn)fn;
  Params P;
  make_map(enc, &P.W[0], d_in[10], 4608, 576, 64, 64);
  make_map(enc, &P.W[1], d_in[11], 4608, 576, 64, 64);
  make_map(enc, &P.Wd, d_in[12], 576, 4608, 64, 96);
  make_map(enc, &P.B[0], d_in[3], 576, 576, 64, 72);
  make_map(enc, &P.B[1], d_in[4], 576, 576, 64, 72);
  make_map(enc, &P.C[0], d_in[5], 576, 576, 64, 64);
  make_map(enc, &P.C[1], d_in[6], 576, 576, 64, 64);
  make_map(enc, &P.C[2], d_in[5], 576, 576, 64, 8);
  make_map(enc, &P.C[3], d_in[6], 576, 576, 64, 8);
  make_map(enc, &P.X, d_in[0], 576, 2048, 64, 128);
  make_map(enc, &P.X8, d_in[0], 576, 2048, 8, 128, false);
  make_map(enc, &P.O, d_out, 576, 2048, 32, 16, true, true);
  make_map(enc, &P.O8, d_out, 576, 2048, 8, 16, false, true);
  void* scr = nullptr;
  cudaGetSymbolAddress(&scr, g_scr);
  cudaFuncSetAttribute(fused_kernel, cudaFuncAttributeMaxDynamicSharedMemorySize, SMEM_BYTES);
  fused_kernel<<<NCTA, 384, SMEM_BYTES, cudaStreamPerThread>>>((Scratch*)scr, (const uint8_t*)d_in[0], (const uint8_t*)d_in[3], (const uint8_t*)d_in[4], (const __nv_bfloat16*)d_in[1],
      (const __nv_bfloat16*)d_in[2], (const __nv_bfloat16*)d_in[7], (const uint32_t*)d_in[8], (float*)d_out, P);
}
```
